```python
import torch

def _softmax(x, axis=-1):
    return torch.softmax(x, dim=axis)

def _gelu(x):
    return torch.nn.functional.gelu(x, approximate='tanh')

def _silu(x):
    return torch.nn.functional.silu(x)

def _sigmoid(x):
    return torch.sigmoid(x)

def _layernorm(x, axis=-1, eps=1e-05):
    m = x.mean(dim=axis, keepdim=True)
    v = x.var(dim=axis, keepdim=True, unbiased=False)
    return (x - m) / torch.sqrt(v + eps)

def _scatter_add(tgt, idx, src, axis=0):
    return tgt.clone().index_add_(axis, idx, src)

def _segment_sum(src, seg, n):
    out = torch.zeros((n,) + src.shape[1:], dtype=src.dtype)
    return out.index_add_(0, seg, src)

def _pad(x, pw):
    flat = tuple((v for pair in reversed(pw) for v in pair))
    return torch.nn.functional.pad(x, flat)
kernel_name = 'parallel_sum__memory_aug_recurrent_mem_tr__glu_gated_bilinear__prompt'

def setup_inputs():

    _w = lambda a: (lambda t: t.to(torch.bfloat16) if t.is_floating_point() else t)(torch.as_tensor(a))

    def _A_setup():
        B, S, Dm = (1, 2048, 640)
        H, Dh = (32, 192)
        M, seg = (8, 32)
        seg = min(seg, S)
        S = S // seg * seg
        return {'x': _w((lambda *s: torch.randn(*s, dtype=torch.bfloat16) * 0.05)(B, S, Dm)), 'mem0': _w((lambda *s: torch.randn(*s, dtype=torch.bfloat16) * 0.2)(B, M, Dm)), 'Wq': _w((lambda *s: torch.randn(*s, dtype=torch.bfloat16) * 1.6)(Dm, H, Dh) * Dm ** (-0.5)), 'Wk': _w((lambda *s: torch.randn(*s, dtype=torch.bfloat16) * 1.6)(Dm, H, Dh) * Dm ** (-0.5)), 'Wv': _w((lambda *s: torch.randn(*s, dtype=torch.bfloat16) * 0.2)(Dm, H, Dh) * Dm ** (-0.5)), 'Wo': _w((lambda *s: torch.randn(*s, dtype=torch.bfloat16) * 0.2)(H, Dh, Dm) * (H * Dh) ** (-0.5)), 'seg_len': seg}
    _A_in = _A_setup()

    def _B_setup():
        B, S, D, F = (1, 2048, 640, 1536)
        return {'x': _w((lambda *s: torch.randn(*s, dtype=torch.bfloat16) * 0.05)(B, S, D)), 'w_gate': _w((lambda *s: torch.randn(*s, dtype=torch.bfloat16) * 0.2)(D, F) * D ** (-0.5)), 'w_up': _w((lambda *s: torch.randn(*s, dtype=torch.bfloat16) * 0.2)(D, F) * D ** (-0.5)), 'w_down': _w((lambda *s: torch.randn(*s, dtype=torch.bfloat16) * 0.2)(F, D) * F ** (-0.5))}
    _B_in = _B_setup()
    return {'A_x': _A_in['x'], 'A_mem0': _A_in['mem0'], 'A_Wq': _A_in['Wq'], 'A_Wk': _A_in['Wk'], 'A_Wv': _A_in['Wv'], 'A_Wo': _A_in['Wo'], 'A_seg_len': _A_in['seg_len'], 'B_x': _B_in['x'], 'B_w_gate': _B_in['w_gate'], 'B_w_up': _B_in['w_up'], 'B_w_down': _B_in['w_down']}

def reference(A_x, A_mem0, A_Wq, A_Wk, A_Wv, A_Wo, A_seg_len, B_x, B_w_gate, B_w_up, B_w_down):

    def _A_ref(x, mem0, Wq, Wk, Wv, Wo, seg_len):
        B, S, Dm = x.shape
        H, Dh = (Wq.shape[1], Wq.shape[2])
        M = mem0.shape[1]
        scale = Dh ** (-0.5)
        n_seg = S // seg_len
        L = M + seg_len
        idx = torch.arange(L)
        mask = (idx[:, None] < M) | (idx[:, None] >= idx[None, :])
        mem = mem0
        outs = []
        for s in range(n_seg):
            xs = x[:, s * seg_len:(s + 1) * seg_len, :].clone()
            h = torch.concatenate([mem, xs], axis=1)
            q = torch.einsum('btd,dhe->bhte', h, Wq)
            k = torch.einsum('btd,dhe->bhte', h, Wk)
            v = torch.einsum('btd,dhe->bhte', h, Wv)
            scores = torch.einsum('bhqe,bhke->bhqk', q, k) * scale
            scores = torch.where(mask[None, None], scores, -1000000000.0)
            p = _softmax(scores, axis=-1)
            o = torch.einsum('bhqk,bhke->bhqe', p, v)
            o = torch.einsum('bhte,hed->btd', o, Wo)
            mem = o[:, :M, :].clone()
            outs.append(o[:, M:, :])
        return torch.concatenate(outs, axis=1)

    def _B_ref(x, w_gate, w_up, w_down):
        g = torch.einsum('bsd,df->bsf', x, w_gate)
        u = torch.einsum('bsd,df->bsf', x, w_up)
        h = g * u
        return torch.einsum('bsf,fd->bsd', h, w_down)
    x = A_x
    xn = _layernorm(x, axis=-1)
    return x + _A_ref(xn, A_mem0, A_Wq, A_Wk, A_Wv, A_Wo, A_seg_len) + _B_ref(xn, B_w_gate, B_w_up, B_w_down)
```

```cpp
#include <climits>
#include <cuda_runtime.h>
#include <cuda_bf16.h>
#include <cuda.h>
#include <stdint.h>

typedef __nv_bfloat16 bf16;

constexpr int S_TOK = 2048, DM = 640, DH = 192, HD = 6144, FF = 1536, NSEG = 64;

__device__ __forceinline__ uint32_t smem_u32(const void* p) { return (uint32_t)__cvta_generic_to_shared(p); }
__device__ __forceinline__ void mbar_init(uint32_t a, uint32_t c) { asm volatile("mbarrier.init.shared::cta.b64 [%0], %1;" :: "r"(a), "r"(c) : "memory"); }
__device__ __forceinline__ void mbar_arrive(uint32_t a) { asm volatile("mbarrier.arrive.shared::cta.b64 _, [%0];" :: "r"(a) : "memory"); }
__device__ __forceinline__ void mbar_expect_tx(uint32_t a, uint32_t bytes) { asm volatile("mbarrier.arrive.expect_tx.shared::cta.b64 _, [%0], %1;" :: "r"(a), "r"(bytes) : "memory"); }
__device__ __forceinline__ void mbar_wait(uint32_t a, uint32_t par) {
    asm volatile("{\n.reg .pred p;\n.reg .u32 n;\nmov.u32 n, 0;\n"
                 "W_%=:\nmbarrier.try_wait.parity.shared::cta.b64 p, [%0], %1;\n@p bra D_%=;\n"
                 "add.u32 n, n, 1;\nsetp.lt.u32 p, n, 200000;\n@p bra W_%=;\ntrap;\nD_%=:\n}" :: "r"(a), "r"(par) : "memory");
}
__device__ __forceinline__ uint32_t mapa(uint32_t a, uint32_t r) { uint32_t o; asm volatile("mapa.shared::cluster.u32 %0, %1, %2;" : "=r"(o) : "r"(a), "r"(r)); return o; }
__device__ __forceinline__ void st_async4(uint32_t d, uint32_t a, uint32_t b, uint32_t c, uint32_t e, uint32_t bar) {
    asm volatile("st.async.shared::cluster.mbarrier::complete_tx::bytes.v4.b32 [%0], {%1,%2,%3,%4}, [%5];" :: "r"(d), "r"(a), "r"(b), "r"(c), "r"(e), "r"(bar) : "memory"); }
__device__ __forceinline__ void st_async2(uint32_t d, uint32_t a, uint32_t b, uint32_t bar) {
    asm volatile("st.async.shared::cluster.mbarrier::complete_tx::bytes.v2.b32 [%0], {%1,%2}, [%3];" :: "r"(d), "r"(a), "r"(b), "r"(bar) : "memory"); }
__device__ __forceinline__ void st_async1(uint32_t d, uint32_t a, uint32_t bar) {
    asm volatile("st.async.shared::cluster.mbarrier::complete_tx::bytes.b32 [%0], %1, [%2];" :: "r"(d), "r"(a), "r"(bar) : "memory"); }
__device__ __forceinline__ void sts4(uint32_t d, uint32_t a, uint32_t b, uint32_t c, uint32_t e) { asm volatile("st.shared.v4.b32 [%0], {%1,%2,%3,%4};" :: "r"(d), "r"(a), "r"(b), "r"(c), "r"(e) : "memory"); }
__device__ __forceinline__ void sts2(uint32_t d, uint32_t a, uint32_t b) { asm volatile("st.shared.v2.b32 [%0], {%1,%2};" :: "r"(d), "r"(a), "r"(b) : "memory"); }
__device__ __forceinline__ void sts1(uint32_t d, uint32_t a) { asm volatile("st.shared.b32 [%0], %1;" :: "r"(d), "r"(a) : "memory"); }
__device__ __forceinline__ uint4 lds4(uint32_t a) { uint4 v; asm volatile("ld.shared.v4.b32 {%0,%1,%2,%3}, [%4];" : "=r"(v.x), "=r"(v.y), "=r"(v.z), "=r"(v.w) : "r"(a) : "memory"); return v; }
__device__ __forceinline__ uint2 lds2(uint32_t a) { uint2 v; asm volatile("ld.shared.v2.b32 {%0,%1}, [%2];" : "=r"(v.x), "=r"(v.y) : "r"(a) : "memory"); return v; }
__device__ __forceinline__ uint32_t lds1(uint32_t a) { uint32_t v; asm volatile("ld.shared.b32 %0, [%1];" : "=r"(v) : "r"(a) : "memory"); return v; }
__device__ __forceinline__ void ldsm4(uint32_t* r, uint32_t a) { asm volatile("ldmatrix.sync.aligned.m8n8.x4.shared.b16 {%0,%1,%2,%3}, [%4];" : "=r"(r[0]), "=r"(r[1]), "=r"(r[2]), "=r"(r[3]) : "r"(a) : "memory"); }
__device__ __forceinline__ void ldsm4t(uint32_t* r, uint32_t a) { asm volatile("ldmatrix.sync.aligned.m8n8.x4.trans.shared.b16 {%0,%1,%2,%3}, [%4];" : "=r"(r[0]), "=r"(r[1]), "=r"(r[2]), "=r"(r[3]) : "r"(a) : "memory"); }
__device__ __forceinline__ void stsm4t(uint32_t a, uint32_t r0, uint32_t r1, uint32_t r2, uint32_t r3) { asm volatile("stmatrix.sync.aligned.m8n8.x4.trans.shared.b16 [%0], {%1,%2,%3,%4};" :: "r"(a), "r"(r0), "r"(r1), "r"(r2), "r"(r3) : "memory"); }
__device__ __forceinline__ void stsm2t(uint32_t a, uint32_t r0, uint32_t r1) { asm volatile("stmatrix.sync.aligned.m8n8.x2.trans.shared.b16 [%0], {%1,%2};" :: "r"(a), "r"(r0), "r"(r1) : "memory"); }
__device__ __forceinline__ uint32_t pack2(float lo, float hi) { uint32_t r; asm("cvt.rn.bf16x2.f32 %0, %1, %2;" : "=r"(r) : "f"(hi), "f"(lo)); return r; }
__device__ __forceinline__ float bf_lo(uint32_t w) { return __uint_as_float(w << 16); }
__device__ __forceinline__ float bf_hi(uint32_t w) { return __uint_as_float(w & 0xFFFF0000u); }
__device__ __forceinline__ float ex2(float x) { float r; asm("ex2.approx.ftz.f32 %0, %1;" : "=f"(r) : "f"(x)); return r; }
__device__ __forceinline__ void mma16(float* d, const uint32_t* a, uint32_t b0, uint32_t b1) {
    asm volatile("mma.sync.aligned.m16n8k16.row.col.f32.bf16.bf16.f32 {%0,%1,%2,%3}, {%4,%5,%6,%7}, {%8,%9}, {%0,%1,%2,%3};"
        : "+f"(d[0]), "+f"(d[1]), "+f"(d[2]), "+f"(d[3]) : "r"(a[0]), "r"(a[1]), "r"(a[2]), "r"(a[3]), "r"(b0), "r"(b1)); }
__device__ __forceinline__ void mma8v(float* d, uint32_t a0, uint32_t a1, uint32_t b0) {
    asm volatile("mma.sync.aligned.m16n8k8.row.col.f32.bf16.bf16.f32 {%0,%1,%2,%3}, {%4,%5}, {%6}, {%0,%1,%2,%3};"
        : "+f"(d[0]), "+f"(d[1]), "+f"(d[2]), "+f"(d[3]) : "r"(a0), "r"(a1), "r"(b0)); }
__device__ __forceinline__ void wg_fence() { asm volatile("wgmma.fence.sync.aligned;" ::: "memory"); }
__device__ __forceinline__ void wg_commit() { asm volatile("wgmma.commit_group.sync.aligned;" ::: "memory"); }
template<int N> __device__ __forceinline__ void wg_wait() { asm volatile("wgmma.wait_group.sync.aligned %0;" :: "n"(N) : "memory"); }
__device__ __forceinline__ void fence_async_smem() { asm volatile("fence.proxy.async.shared::cta;" ::: "memory"); }
__device__ __forceinline__ void fence_async_all() { asm volatile("fence.proxy.async;" ::: "memory"); }
__device__ __forceinline__ void bar_sync(int id, int n) { asm volatile("bar.sync %0, %1;" :: "r"(id), "r"(n) : "memory"); }
__device__ __forceinline__ uint64_t mkdesc(uint32_t a, uint32_t lbo, uint32_t sbo, uint32_t sw) {
    return (uint64_t)((a & 0x3FFFF) >> 4) | ((uint64_t)(lbo >> 4) << 16) | ((uint64_t)(sbo >> 4) << 32) | ((uint64_t)sw << 62); }
__device__ __forceinline__ void tma2d(uint32_t dst, const CUtensorMap* m, int c0, int c1, uint32_t bar) {
    asm volatile("cp.async.bulk.tensor.2d.shared::cluster.global.mbarrier::complete_tx::bytes [%0], [%1, {%3, %4}], [%2];"
        :: "r"(dst), "l"((uint64_t)m), "r"(bar), "r"(c0), "r"(c1) : "memory"); }
__device__ __forceinline__ uint32_t clk32() { uint32_t c; asm volatile("mov.u32 %0, %%clock;" : "=r"(c) :: "memory"); return c; }

__device__ __forceinline__ void wg_rs32_a(float* d, const uint32_t* a, uint64_t db) {
    asm volatile("wgmma.mma_async.sync.aligned.m64n32k16.f32.bf16.bf16 {%0,%1,%2,%3,%4,%5,%6,%7,%8,%9,%10,%11,%12,%13,%14,%15}, {%16,%17,%18,%19}, %20, 1, 1, 1, 0;"
        : "+f"(d[0]), "+f"(d[1]), "+f"(d[2]), "+f"(d[3]), "+f"(d[4]), "+f"(d[5]), "+f"(d[6]), "+f"(d[7]), "+f"(d[8]), "+f"(d[9]), "+f"(d[10]), "+f"(d[11]), "+f"(d[12]), "+f"(d[13]), "+f"(d[14]), "+f"(d[15])
        : "r"(a[0]), "r"(a[1]), "r"(a[2]), "r"(a[3]), "l"(db)); }
__device__ __forceinline__ void wg_ss40_z(float* d, uint64_t da, uint64_t db) {
    asm volatile("wgmma.mma_async.sync.aligned.m64n40k16.f32.bf16.bf16 {%0,%1,%2,%3,%4,%5,%6,%7,%8,%9,%10,%11,%12,%13,%14,%15,%16,%17,%18,%19}, %20, %21, 0, 1, 1, 1, 0;"
        : "=f"(d[0]), "=f"(d[1]), "=f"(d[2]), "=f"(d[3]), "=f"(d[4]), "=f"(d[5]), "=f"(d[6]), "=f"(d[7]), "=f"(d[8]), "=f"(d[9]), "=f"(d[10]), "=f"(d[11]), "=f"(d[12]), "=f"(d[13]), "=f"(d[14]), "=f"(d[15]), "=f"(d[16]), "=f"(d[17]), "=f"(d[18]), "=f"(d[19])
        : "l"(da), "l"(db)); }
__device__ __forceinline__ void wg_ss40_a(float* d, uint64_t da, uint64_t db) {
    asm volatile("wgmma.mma_async.sync.aligned.m64n40k16.f32.bf16.bf16 {%0,%1,%2,%3,%4,%5,%6,%7,%8,%9,%10,%11,%12,%13,%14,%15,%16,%17,%18,%19}, %20, %21, 1, 1, 1, 1, 0;"
        : "+f"(d[0]), "+f"(d[1]), "+f"(d[2]), "+f"(d[3]), "+f"(d[4]), "+f"(d[5]), "+f"(d[6]), "+f"(d[7]), "+f"(d[8]), "+f"(d[9]), "+f"(d[10]), "+f"(d[11]), "+f"(d[12]), "+f"(d[13]), "+f"(d[14]), "+f"(d[15]), "+f"(d[16]), "+f"(d[17]), "+f"(d[18]), "+f"(d[19])
        : "l"(da), "l"(db)); }
__device__ __forceinline__ void wg_ss40(float* d, uint64_t da, uint64_t db, bool acc) { if (acc) wg_ss40_a(d, da, db); else wg_ss40_z(d, da, db); }
__device__ __forceinline__ void wg_ss8_z(float* d, uint64_t da, uint64_t db) {
    asm volatile("wgmma.mma_async.sync.aligned.m64n8k16.f32.bf16.bf16 {%0,%1,%2,%3}, %4, %5, 0, 1, 1, 1, 1;"
        : "=f"(d[0]), "=f"(d[1]), "=f"(d[2]), "=f"(d[3])
        : "l"(da), "l"(db)); }
__device__ __forceinline__ void wg_ss8_a(float* d, uint64_t da, uint64_t db) {
    asm volatile("wgmma.mma_async.sync.aligned.m64n8k16.f32.bf16.bf16 {%0,%1,%2,%3}, %4, %5, 1, 1, 1, 1, 1;"
        : "+f"(d[0]), "+f"(d[1]), "+f"(d[2]), "+f"(d[3])
        : "l"(da), "l"(db)); }
__device__ __forceinline__ void wg_ss8(float* d, uint64_t da, uint64_t db, bool acc) { if (acc) wg_ss8_a(d, da, db); else wg_ss8_z(d, da, db); }
__device__ __forceinline__ void wg_kk32_z(float* d, uint64_t da, uint64_t db) {
    asm volatile("wgmma.mma_async.sync.aligned.m64n32k16.f32.bf16.bf16 {%0,%1,%2,%3,%4,%5,%6,%7,%8,%9,%10,%11,%12,%13,%14,%15}, %16, %17, 0, 1, 1, 0, 0;"
        : "=f"(d[0]), "=f"(d[1]), "=f"(d[2]), "=f"(d[3]), "=f"(d[4]), "=f"(d[5]), "=f"(d[6]), "=f"(d[7]), "=f"(d[8]), "=f"(d[9]), "=f"(d[10]), "=f"(d[11]), "=f"(d[12]), "=f"(d[13]), "=f"(d[14]), "=f"(d[15])
        : "l"(da), "l"(db)); }
__device__ __forceinline__ void wg_kk32_a(float* d, uint64_t da, uint64_t db) {
    asm volatile("wgmma.mma_async.sync.aligned.m64n32k16.f32.bf16.bf16 {%0,%1,%2,%3,%4,%5,%6,%7,%8,%9,%10,%11,%12,%13,%14,%15}, %16, %17, 1, 1, 1, 0, 0;"
        : "+f"(d[0]), "+f"(d[1]), "+f"(d[2]), "+f"(d[3]), "+f"(d[4]), "+f"(d[5]), "+f"(d[6]), "+f"(d[7]), "+f"(d[8]), "+f"(d[9]), "+f"(d[10]), "+f"(d[11]), "+f"(d[12]), "+f"(d[13]), "+f"(d[14]), "+f"(d[15])
        : "l"(da), "l"(db)); }
__device__ __forceinline__ void wg_kk32(float* d, uint64_t da, uint64_t db, bool acc) { if (acc) wg_kk32_a(d, da, db); else wg_kk32_z(d, da, db); }
__device__ __forceinline__ uint32_t fu(float x) { return __float_as_uint(x); }
__device__ __forceinline__ float uf(uint32_t x) { return __uint_as_float(x); }
__device__ __forceinline__ void st_async4_p(bool p, uint32_t d, uint32_t a, uint32_t b, uint32_t c, uint32_t e, uint32_t bar) {
    asm volatile("{.reg .pred p; setp.ne.b32 p, %6, 0;\n@p st.async.shared::cluster.mbarrier::complete_tx::bytes.v4.b32 [%0], {%1,%2,%3,%4}, [%5];}"
        :: "r"(d), "r"(a), "r"(b), "r"(c), "r"(e), "r"(bar), "r"((uint32_t)p) : "memory"); }
__device__ __forceinline__ void st_async2_p(bool p, uint32_t d, uint32_t a, uint32_t b, uint32_t bar) {
    asm volatile("{.reg .pred p; setp.ne.b32 p, %4, 0;\n@p st.async.shared::cluster.mbarrier::complete_tx::bytes.v2.b32 [%0], {%1,%2}, [%3];}"
        :: "r"(d), "r"(a), "r"(b), "r"(bar), "r"((uint32_t)p) : "memory"); }
__device__ __forceinline__ void sts4_p(bool p, uint32_t d, uint32_t a, uint32_t b, uint32_t c, uint32_t e) {
    asm volatile("{.reg .pred p; setp.ne.b32 p, %5, 0;\n@p st.shared.v4.b32 [%0], {%1,%2,%3,%4};}" :: "r"(d), "r"(a), "r"(b), "r"(c), "r"(e), "r"((uint32_t)p) : "memory"); }
__device__ __forceinline__ void sts2_p(bool p, uint32_t d, uint32_t a, uint32_t b) {
    asm volatile("{.reg .pred p; setp.ne.b32 p, %3, 0;\n@p st.shared.v2.b32 [%0], {%1,%2};}" :: "r"(d), "r"(a), "r"(b), "r"((uint32_t)p) : "memory"); }
__device__ __forceinline__ void mbar_arrive_p(bool p, uint32_t a) {
    asm volatile("{.reg .pred p; setp.ne.b32 p, %1, 0;\n@p mbarrier.arrive.shared::cta.b64 _, [%0];}" :: "r"(a), "r"((uint32_t)p) : "memory"); }
__device__ __forceinline__ void mbar_expect_tx_p(bool p, uint32_t a, uint32_t bytes) {
    asm volatile("{.reg .pred p; setp.ne.b32 p, %2, 0;\n@p mbarrier.arrive.expect_tx.shared::cta.b64 _, [%0], %1;}" :: "r"(a), "r"(bytes), "r"((uint32_t)p) : "memory"); }
__device__ __forceinline__ float rcp_approx(float x) { float r; asm("rcp.approx.ftz.f32 %0, %1;" : "=f"(r) : "f"(x)); return r; }
template<int LUT> __device__ __forceinline__ uint32_t lop3(uint32_t a, uint32_t b, uint32_t c) { uint32_t r; asm("lop3.b32 %0, %1, %2, %3, %4;" : "=r"(r) : "r"(a), "r"(b), "r"(c), "n"(LUT)); return r; }
__device__ __forceinline__ uint32_t or_xor(uint32_t a, uint32_t b, uint32_t c) { return lop3<0xF0 | (0xCC ^ 0xAA)>(a, b, c); }
__device__ __forceinline__ uint32_t set_tag(float a, uint32_t t) { return lop3<(0xF0 & 0xCC) | 0xAA>(__float_as_uint(a), 0xFFFFFFFEu, t); }
__device__ __forceinline__ void bulk_g2s(uint32_t dst, const void* src, uint32_t bytes, uint32_t bar) {
    asm volatile("cp.async.bulk.shared::cluster.global.mbarrier::complete_tx::bytes [%0], [%1], %2, [%3];" :: "r"(dst), "l"(src), "r"(bytes), "r"(bar) : "memory"); }
__device__ __forceinline__ void bar_arrive(int id, int n) { asm volatile("bar.arrive %0, %1;" :: "r"(id), "r"(n) : "memory"); }
__device__ __forceinline__ void stg_a64(void* p, uint32_t a, uint32_t b) {
    asm volatile("{.reg .b64 t; mov.b64 t, {%1,%2}; st.relaxed.gpu.global.b64 [%0], t;}" :: "l"(p), "r"(a), "r"(b) : "memory"); }
__device__ __forceinline__ void ldsm2t(uint32_t* r, uint32_t a) { asm volatile("ldmatrix.sync.aligned.m8n8.x2.trans.shared.b16 {%0,%1}, [%2];" : "=r"(r[0]), "=r"(r[1]) : "r"(a) : "memory"); }
constexpr uint32_t SB0 = 1024;
__host__ __device__ constexpr uint64_t cdesc(uint32_t off, uint32_t lbo, uint32_t sbo, uint32_t sw) {
    return (uint64_t)(((SB0 + off) & 0x3FFFF) >> 4) | ((uint64_t)(lbo >> 4) << 16) | ((uint64_t)(sbo >> 4) << 32) | ((uint64_t)sw << 62); }
__device__ __forceinline__ void ldg_a64_retry(uint2& v, const void* p, uint32_t tag) {
    asm volatile("{.reg .pred p; .reg .b32 x; .reg .b64 t; lop3.b32 x, %0, %3, 1, 0x28; setp.ne.b32 p, x, 0;\n"
                 "mov.b64 t, {%0,%1};\n@p ld.relaxed.gpu.global.b64 t, [%2];\nmov.b64 {%0,%1}, t;}"
                 : "+r"(v.x), "+r"(v.y) : "l"(p), "r"(tag) : "memory"); }
__device__ __forceinline__ bool mbar_test(uint32_t a, uint32_t par) {
    uint32_t p;
    asm volatile("{.reg .pred p; mbarrier.test_wait.parity.shared::cta.b64 p, [%1], %2; selp.u32 %0,1,0,p;}" : "=r"(p) : "r"(a), "r"(par) : "memory");
    return p;
}
__device__ __forceinline__ void wg_rt32_z(float* d, const uint32_t* a, uint64_t db) {
    asm volatile("wgmma.mma_async.sync.aligned.m64n32k16.f32.bf16.bf16 {%0,%1,%2,%3,%4,%5,%6,%7,%8,%9,%10,%11,%12,%13,%14,%15}, {%16,%17,%18,%19}, %20, 0, 1, 1, 1;"
        : "=f"(d[0]), "=f"(d[1]), "=f"(d[2]), "=f"(d[3]), "=f"(d[4]), "=f"(d[5]), "=f"(d[6]), "=f"(d[7]), "=f"(d[8]), "=f"(d[9]), "=f"(d[10]), "=f"(d[11]), "=f"(d[12]), "=f"(d[13]), "=f"(d[14]), "=f"(d[15])
        : "r"(a[0]), "r"(a[1]), "r"(a[2]), "r"(a[3]), "l"(db)); }
__device__ __forceinline__ void wg_rt32_a(float* d, const uint32_t* a, uint64_t db) {
    asm volatile("wgmma.mma_async.sync.aligned.m64n32k16.f32.bf16.bf16 {%0,%1,%2,%3,%4,%5,%6,%7,%8,%9,%10,%11,%12,%13,%14,%15}, {%16,%17,%18,%19}, %20, 1, 1, 1, 1;"
        : "+f"(d[0]), "+f"(d[1]), "+f"(d[2]), "+f"(d[3]), "+f"(d[4]), "+f"(d[5]), "+f"(d[6]), "+f"(d[7]), "+f"(d[8]), "+f"(d[9]), "+f"(d[10]), "+f"(d[11]), "+f"(d[12]), "+f"(d[13]), "+f"(d[14]), "+f"(d[15])
        : "r"(a[0]), "r"(a[1]), "r"(a[2]), "r"(a[3]), "l"(db)); }
__device__ __forceinline__ void mbar_wait_long(uint32_t a, uint32_t par) {
    asm volatile("{\n.reg .pred p;\n.reg .u32 n;\nmov.u32 n, 0;\n"
                 "W_%=:\nmbarrier.try_wait.parity.shared::cta.b64 p, [%0], %1;\n@p bra D_%=;\n"
                 "add.u32 n, n, 1;\nsetp.lt.u32 p, n, 1000000;\n@p bra W_%=;\ntrap;\nD_%=:\n}" :: "r"(a), "r"(par) : "memory");
}
__device__ __forceinline__ void ldg_a64_p(bool p, uint2& v, const void* ptr) {
    asm volatile("{.reg .pred p; .reg .b64 t; setp.ne.b32 p, %3, 0;\nmov.b64 t, {%0,%1};\n@p ld.relaxed.gpu.global.b64 t, [%2];\nmov.b64 {%0,%1}, t;}"
                 : "+r"(v.x), "+r"(v.y) : "l"(ptr), "r"((uint32_t)p) : "memory"); }
__device__ __forceinline__ uint32_t hadd2(uint32_t a, uint32_t b) { uint32_t r; asm("add.rn.bf16x2 %0, %1, %2;" : "=r"(r) : "r"(a), "r"(b)); return r; }
__device__ __forceinline__ void wg_rs40_a(float* d, const uint32_t* a, uint64_t db) {
    asm volatile("wgmma.mma_async.sync.aligned.m64n40k16.f32.bf16.bf16 {%0,%1,%2,%3,%4,%5,%6,%7,%8,%9,%10,%11,%12,%13,%14,%15,%16,%17,%18,%19}, {%20,%21,%22,%23}, %24, 1, 1, 1, 0;"
        : "+f"(d[0]), "+f"(d[1]), "+f"(d[2]), "+f"(d[3]), "+f"(d[4]), "+f"(d[5]), "+f"(d[6]), "+f"(d[7]), "+f"(d[8]), "+f"(d[9]), "+f"(d[10]), "+f"(d[11]), "+f"(d[12]), "+f"(d[13]), "+f"(d[14]), "+f"(d[15]), "+f"(d[16]), "+f"(d[17]), "+f"(d[18]), "+f"(d[19])
        : "r"(a[0]), "r"(a[1]), "r"(a[2]), "r"(a[3]), "l"(db)); }
__device__ __forceinline__ void wg_g256(float* d, uint64_t da, uint64_t db) {
    asm volatile("wgmma.mma_async.sync.aligned.m64n256k16.f32.bf16.bf16 {%0,%1,%2,%3,%4,%5,%6,%7,%8,%9,%10,%11,%12,%13,%14,%15,%16,%17,%18,%19,%20,%21,%22,%23,%24,%25,%26,%27,%28,%29,%30,%31,%32,%33,%34,%35,%36,%37,%38,%39,%40,%41,%42,%43,%44,%45,%46,%47,%48,%49,%50,%51,%52,%53,%54,%55,%56,%57,%58,%59,%60,%61,%62,%63,%64,%65,%66,%67,%68,%69,%70,%71,%72,%73,%74,%75,%76,%77,%78,%79,%80,%81,%82,%83,%84,%85,%86,%87,%88,%89,%90,%91,%92,%93,%94,%95,%96,%97,%98,%99,%100,%101,%102,%103,%104,%105,%106,%107,%108,%109,%110,%111,%112,%113,%114,%115,%116,%117,%118,%119,%120,%121,%122,%123,%124,%125,%126,%127}, %128, %129, 1, 1, 1, 0, 1;"
        : "+f"(d[0]), "+f"(d[1]), "+f"(d[2]), "+f"(d[3]), "+f"(d[4]), "+f"(d[5]), "+f"(d[6]), "+f"(d[7]), "+f"(d[8]), "+f"(d[9]), "+f"(d[10]), "+f"(d[11]), "+f"(d[12]), "+f"(d[13]), "+f"(d[14]), "+f"(d[15]), "+f"(d[16]), "+f"(d[17]), "+f"(d[18]), "+f"(d[19]), "+f"(d[20]), "+f"(d[21]), "+f"(d[22]), "+f"(d[23]), "+f"(d[24]), "+f"(d[25]), "+f"(d[26]), "+f"(d[27]), "+f"(d[28]), "+f"(d[29]), "+f"(d[30]), "+f"(d[31]), "+f"(d[32]), "+f"(d[33]), "+f"(d[34]), "+f"(d[35]), "+f"(d[36]), "+f"(d[37]), "+f"(d[38]), "+f"(d[39]), "+f"(d[40]), "+f"(d[41]), "+f"(d[42]), "+f"(d[43]), "+f"(d[44]), "+f"(d[45]), "+f"(d[46]), "+f"(d[47]), "+f"(d[48]), "+f"(d[49]), "+f"(d[50]), "+f"(d[51]), "+f"(d[52]), "+f"(d[53]), "+f"(d[54]), "+f"(d[55]), "+f"(d[56]), "+f"(d[57]), "+f"(d[58]), "+f"(d[59]), "+f"(d[60]), "+f"(d[61]), "+f"(d[62]), "+f"(d[63]), "+f"(d[64]), "+f"(d[65]), "+f"(d[66]), "+f"(d[67]), "+f"(d[68]), "+f"(d[69]), "+f"(d[70]), "+f"(d[71]), "+f"(d[72]), "+f"(d[73]), "+f"(d[74]), "+f"(d[75]), "+f"(d[76]), "+f"(d[77]), "+f"(d[78]), "+f"(d[79]), "+f"(d[80]), "+f"(d[81]), "+f"(d[82]), "+f"(d[83]), "+f"(d[84]), "+f"(d[85]), "+f"(d[86]), "+f"(d[87]), "+f"(d[88]), "+f"(d[89]), "+f"(d[90]), "+f"(d[91]), "+f"(d[92]), "+f"(d[93]), "+f"(d[94]), "+f"(d[95]), "+f"(d[96]), "+f"(d[97]), "+f"(d[98]), "+f"(d[99]), "+f"(d[100]), "+f"(d[101]), "+f"(d[102]), "+f"(d[103]), "+f"(d[104]), "+f"(d[105]), "+f"(d[106]), "+f"(d[107]), "+f"(d[108]), "+f"(d[109]), "+f"(d[110]), "+f"(d[111]), "+f"(d[112]), "+f"(d[113]), "+f"(d[114]), "+f"(d[115]), "+f"(d[116]), "+f"(d[117]), "+f"(d[118]), "+f"(d[119]), "+f"(d[120]), "+f"(d[121]), "+f"(d[122]), "+f"(d[123]), "+f"(d[124]), "+f"(d[125]), "+f"(d[126]), "+f"(d[127])
        : "l"(da), "l"(db)); }
__device__ __forceinline__ void wg_g192(float* d, uint64_t da, uint64_t db) {
    asm volatile("wgmma.mma_async.sync.aligned.m64n192k16.f32.bf16.bf16 {%0,%1,%2,%3,%4,%5,%6,%7,%8,%9,%10,%11,%12,%13,%14,%15,%16,%17,%18,%19,%20,%21,%22,%23,%24,%25,%26,%27,%28,%29,%30,%31,%32,%33,%34,%35,%36,%37,%38,%39,%40,%41,%42,%43,%44,%45,%46,%47,%48,%49,%50,%51,%52,%53,%54,%55,%56,%57,%58,%59,%60,%61,%62,%63,%64,%65,%66,%67,%68,%69,%70,%71,%72,%73,%74,%75,%76,%77,%78,%79,%80,%81,%82,%83,%84,%85,%86,%87,%88,%89,%90,%91,%92,%93,%94,%95}, %96, %97, 1, 1, 1, 0, 1;"
        : "+f"(d[0]), "+f"(d[1]), "+f"(d[2]), "+f"(d[3]), "+f"(d[4]), "+f"(d[5]), "+f"(d[6]), "+f"(d[7]), "+f"(d[8]), "+f"(d[9]), "+f"(d[10]), "+f"(d[11]), "+f"(d[12]), "+f"(d[13]), "+f"(d[14]), "+f"(d[15]), "+f"(d[16]), "+f"(d[17]), "+f"(d[18]), "+f"(d[19]), "+f"(d[20]), "+f"(d[21]), "+f"(d[22]), "+f"(d[23]), "+f"(d[24]), "+f"(d[25]), "+f"(d[26]), "+f"(d[27]), "+f"(d[28]), "+f"(d[29]), "+f"(d[30]), "+f"(d[31]), "+f"(d[32]), "+f"(d[33]), "+f"(d[34]), "+f"(d[35]), "+f"(d[36]), "+f"(d[37]), "+f"(d[38]), "+f"(d[39]), "+f"(d[40]), "+f"(d[41]), "+f"(d[42]), "+f"(d[43]), "+f"(d[44]), "+f"(d[45]), "+f"(d[46]), "+f"(d[47]), "+f"(d[48]), "+f"(d[49]), "+f"(d[50]), "+f"(d[51]), "+f"(d[52]), "+f"(d[53]), "+f"(d[54]), "+f"(d[55]), "+f"(d[56]), "+f"(d[57]), "+f"(d[58]), "+f"(d[59]), "+f"(d[60]), "+f"(d[61]), "+f"(d[62]), "+f"(d[63]), "+f"(d[64]), "+f"(d[65]), "+f"(d[66]), "+f"(d[67]), "+f"(d[68]), "+f"(d[69]), "+f"(d[70]), "+f"(d[71]), "+f"(d[72]), "+f"(d[73]), "+f"(d[74]), "+f"(d[75]), "+f"(d[76]), "+f"(d[77]), "+f"(d[78]), "+f"(d[79]), "+f"(d[80]), "+f"(d[81]), "+f"(d[82]), "+f"(d[83]), "+f"(d[84]), "+f"(d[85]), "+f"(d[86]), "+f"(d[87]), "+f"(d[88]), "+f"(d[89]), "+f"(d[90]), "+f"(d[91]), "+f"(d[92]), "+f"(d[93]), "+f"(d[94]), "+f"(d[95])
        : "l"(da), "l"(db)); }
__device__ __forceinline__ void wg_g128(float* d, uint64_t da, uint64_t db) {
    asm volatile("wgmma.mma_async.sync.aligned.m64n128k16.f32.bf16.bf16 {%0,%1,%2,%3,%4,%5,%6,%7,%8,%9,%10,%11,%12,%13,%14,%15,%16,%17,%18,%19,%20,%21,%22,%23,%24,%25,%26,%27,%28,%29,%30,%31,%32,%33,%34,%35,%36,%37,%38,%39,%40,%41,%42,%43,%44,%45,%46,%47,%48,%49,%50,%51,%52,%53,%54,%55,%56,%57,%58,%59,%60,%61,%62,%63}, %64, %65, 1, 1, 1, 0, 1;"
        : "+f"(d[0]), "+f"(d[1]), "+f"(d[2]), "+f"(d[3]), "+f"(d[4]), "+f"(d[5]), "+f"(d[6]), "+f"(d[7]), "+f"(d[8]), "+f"(d[9]), "+f"(d[10]), "+f"(d[11]), "+f"(d[12]), "+f"(d[13]), "+f"(d[14]), "+f"(d[15]), "+f"(d[16]), "+f"(d[17]), "+f"(d[18]), "+f"(d[19]), "+f"(d[20]), "+f"(d[21]), "+f"(d[22]), "+f"(d[23]), "+f"(d[24]), "+f"(d[25]), "+f"(d[26]), "+f"(d[27]), "+f"(d[28]), "+f"(d[29]), "+f"(d[30]), "+f"(d[31]), "+f"(d[32]), "+f"(d[33]), "+f"(d[34]), "+f"(d[35]), "+f"(d[36]), "+f"(d[37]), "+f"(d[38]), "+f"(d[39]), "+f"(d[40]), "+f"(d[41]), "+f"(d[42]), "+f"(d[43]), "+f"(d[44]), "+f"(d[45]), "+f"(d[46]), "+f"(d[47]), "+f"(d[48]), "+f"(d[49]), "+f"(d[50]), "+f"(d[51]), "+f"(d[52]), "+f"(d[53]), "+f"(d[54]), "+f"(d[55]), "+f"(d[56]), "+f"(d[57]), "+f"(d[58]), "+f"(d[59]), "+f"(d[60]), "+f"(d[61]), "+f"(d[62]), "+f"(d[63])
        : "l"(da), "l"(db)); }
constexpr int G_STAGES = 4, G_STAGE_BYTES = 57344, G_SMEM = G_STAGES * G_STAGE_BYTES + 256;
constexpr int NTB = 16;
__host__ __device__ constexpr int osplit(int tb) { return tb < 9 ? 2 : (tb < 12 ? 4 : (tb < 15 ? 8 : 16)); }
__host__ __device__ constexpr int rsplit(int tb) { return tb < 9 ? 1 : (tb < 12 ? 2 : (tb < 15 ? 5 : 20)); }
__host__ __device__ constexpr int slot0(int tb) { int s = 0; for (int i = 0; i < tb; i++) s += 2 * (osplit(i) + 1); return s; }
constexpr int NSLOT = slot0(NTB);
struct TaskTable { int n; unsigned t[600]; };
constexpr TaskTable make_tasks() {
    TaskTable T = {}; int n = 0;
    for (int tb = 0; tb < NTB; tb++) for (int j = 0; j < 12; j++) T.t[n++] = 0 | tb << 2 | j << 6;
    for (int tb = 0; tb < NTB; tb++) for (int j = 0; j < 2; j++) T.t[n++] = 1 | tb << 2 | j << 6;
    for (int tb = 0; tb <= NTB; tb++) {
        for (int rb = 0; rb < NTB; rb++) {
            const int at = rb < 9 ? rb + 4 : (rb < 12 ? rb + 2 : rb + 1);
            if (at == tb && rb < NTB - 1) for (int p = 0; p < rsplit(rb); p++) for (int j = 0; j < 2; j++) T.t[n++] = 3 | rb << 2 | j << 6 | p << 10;
        }
        if (tb < NTB - 1) for (int p = 0; p < osplit(tb); p++) for (int j = 0; j < 2; j++) T.t[n++] = 2 | tb << 2 | j << 6 | p << 10;
    }
    for (int h = 1; h <= 2; h++) for (int p = 0; p < 16; p++) for (int j = 0; j < 2; j++) T.t[n++] = 2 | 15 << 2 | j << 6 | p << 10 | h << 16;
    for (int h = 1; h <= 2; h++) for (int p = 0; p < 20; p++) for (int j = 0; j < 2; j++) T.t[n++] = 3 | 15 << 2 | j << 6 | p << 10 | h << 16;
    T.n = n; return T;
}
__constant__ TaskTable c_tasks = make_tasks();
constexpr int T_TOTAL = make_tasks().n;
__device__ __align__(128) bf16 g_h[S_TOK * FF];
__device__ uint4 g_ps[NSLOT * 20 * 256];
struct Flags { unsigned task, done, o_ready[NTB + 1], h_ready[NTB], tile[NTB * 2 + 2]; };
__device__ Flags g_fl;

__device__ __forceinline__ unsigned ld_acq(const unsigned* p) { unsigned v; asm volatile("ld.acquire.gpu.global.u32 %0, [%1];" : "=r"(v) : "l"(p) : "memory"); return v; }
__device__ __forceinline__ void wait_flag(const unsigned* p, unsigned target) {
    unsigned n = 0;
    while (ld_acq(p) < target) { __nanosleep(64); if (++n > 20000000u) __trap(); }
}

template<int NP, int JU>
__device__ __forceinline__ void reduce_cols(const uint4* pp, const bf16* x, bf16* out, int j0, int jn, bool od) {
    #pragma unroll 1
    for (int j = j0; j < j0 + jn; j += 2 * JU) {
        uint4 u[JU][NP]; uint2 xv[JU][2];
        #pragma unroll
        for (int i = 0; i < JU; i++) {
            #pragma unroll
            for (int p = 0; p < NP; p++) u[i][p] = __ldcg(pp + p * 5120 + (j / 2 + i) * 256);
            xv[i][0] = *reinterpret_cast<const uint2*>(x + 8 * (j + 2 * i)); xv[i][1] = *reinterpret_cast<const uint2*>(x + 8 * (j + 2 * i) + 8 * DM);
        }
        #pragma unroll
        for (int i = 0; i < JU; i++) {
            float4 a = make_float4(0.f, 0.f, 0.f, 0.f), b = a;
            #pragma unroll
            for (int p = 0; p < NP; p++) {
                a.x += bf_lo(u[i][p].x); a.y += bf_hi(u[i][p].x); a.z += bf_lo(u[i][p].y); a.w += bf_hi(u[i][p].y);
                b.x += bf_lo(u[i][p].z); b.y += bf_hi(u[i][p].z); b.z += bf_lo(u[i][p].w); b.w += bf_hi(u[i][p].w);
            }
            const float r0 = __shfl_xor_sync(~0u, od ? a.x : b.x, 1), r1 = __shfl_xor_sync(~0u, od ? a.y : b.y, 1),
                        r2 = __shfl_xor_sync(~0u, od ? a.z : b.z, 1), r3 = __shfl_xor_sync(~0u, od ? a.w : b.w, 1);
            const float t0 = od ? r0 : a.x, t1 = od ? r1 : a.y, t2 = od ? b.x : r0, t3 = od ? b.y : r1;
            const float u0 = od ? r2 : a.z, u1 = od ? r3 : a.w, u2 = od ? b.z : r2, u3 = od ? b.w : r3;
            const uint2 x0 = xv[i][0], x1 = xv[i][1];
            *reinterpret_cast<uint2*>(out + 8 * (j + 2 * i)) = make_uint2(pack2(bf_lo(x0.x) + t0, bf_hi(x0.x) + t1), pack2(bf_lo(x0.y) + t2, bf_hi(x0.y) + t3));
            *reinterpret_cast<uint2*>(out + 8 * (j + 2 * i) + 8 * DM) = make_uint2(pack2(bf_lo(x1.x) + u0, bf_hi(x1.x) + u1), pack2(bf_lo(x1.y) + u2, bf_hi(x1.y) + u3));
        }
    }
}

__global__ void __launch_bounds__(384, 1)
g_kernel(const __grid_constant__ CUtensorMap tmX, const __grid_constant__ CUtensorMap tmH, const __grid_constant__ CUtensorMap tmOa,
         const __grid_constant__ CUtensorMap tmG, const __grid_constant__ CUtensorMap tmU, const __grid_constant__ CUtensorMap tmD,
         const __grid_constant__ CUtensorMap tmWo, const __grid_constant__ CUtensorMap tmOh, const bf16* __restrict__ x, bf16* __restrict__ out, unsigned o_target)
{
    extern __shared__ __align__(1024) unsigned char smem[];
    const uint32_t sb = smem_u32(smem), bar = sb + G_STAGES * G_STAGE_BYTES;
    const int tid = threadIdx.x, warp = __shfl_sync(~0u, tid >> 5, 0), lane = tid & 31;
    if (tid == 0) {
        for (int i = 0; i < G_STAGES; i++) { mbar_init(bar + 8 * i, 1); mbar_init(bar + 32 + 8 * i, 8); }
        for (int i = 0; i < 2; i++) { mbar_init(bar + 64 + 8 * i, 1); mbar_init(bar + 80 + 8 * i, 8); }
        asm volatile("fence.mbarrier_init.release.cluster;" ::: "memory");
    }
    __syncthreads();
    if (warp >= 8) {
        asm volatile("setmaxnreg.dec.sync.aligned.u32 40;");
        if (warp == 8) {
            uint32_t it = 0;
            for (uint32_t n = 0;; n++) {
                int t = 0;
                if (lane == 0) t = (int)atomicAdd(&g_fl.task, 1u);
                t = __shfl_sync(~0u, t, 0);
                const uint32_t tw = t < T_TOTAL ? c_tasks.t[t] : 0xFFFFFFFFu;
                const int kind = tw & 3, tb = (tw >> 2) & 15, nn = (tw >> 6) & 15, part = (tw >> 10) & 63, half = (tw >> 16) & 3;
                const unsigned* flag = kind == 1 ? &g_fl.h_ready[tb] : (kind == 2 ? &g_fl.o_ready[tb + (half == 1)] : &g_fl.tile[(tb + (half == 1)) * 2 + nn]);
                const unsigned target = kind == 0 ? 0u : (kind == 1 ? 12u : (kind == 2 ? o_target : (unsigned)osplit(tb) + 1));
                if (t < T_TOTAL && kind == 3) { if (lane == 0) wait_flag(flag, target); __syncwarp(); }
                mbar_wait_long(bar + 80 + 8 * (n & 1), ((n >> 1) & 1) ^ 1);
                if (lane == 0) { sts1(bar + 96 + 4 * (n & 1), tw); mbar_arrive(bar + 64 + 8 * (n & 1)); }
                if (t >= T_TOTAL) break;
                if (kind == 3) continue;
                const int nk = kind == 0 ? 10 : (kind == 1 ? 24 : 96 / osplit(tb)), k0 = kind == 2 ? part * nk : 0;
                const CUtensorMap* mp = lane == 0 ? (kind == 0 ? &tmX : (kind == 1 ? &tmH : (half ? &tmOh : &tmOa)))
                                                  : (kind == 0 ? (lane < 3 ? &tmG : &tmU) : (kind == 1 ? &tmD : &tmWo));
                const int fix = lane == 0 ? tb * 128 + (half == 2 ? 64 : 0) : (kind == 0 ? nn * 128 + ((lane - 1) & 1) * 64 : nn * 320 + (lane - 1) * 64);
                const uint32_t doff = lane == 0 ? (half == 2 ? 8192 : 0) : 8192 + lane * 8192;
                const int nl = kind == 0 ? 5 : 6;
                bool ready = kind == 0;
                if (!ready) ready = __shfl_sync(~0u, lane == 0 ? (int)(ld_acq(flag) >= target) : 0, 0);
                if (ready) fence_async_all();
                for (int kb = 0; kb < nk; kb++, it++) {
                    const uint32_t st = it % G_STAGES, fb = bar + 8 * st;
                    if (!ready && kb == G_STAGES) ready = true;
                    mbar_wait_long(bar + 32 + 8 * st, ((it / G_STAGES) & 1) ^ 1);
                    const int kc = (k0 + kb) * 64;
                    if (lane == 0) mbar_expect_tx(fb, (half ? 0 : 8192) + nl * 8192);
                    __syncwarp();
                    if (lane < nl && (ready || lane > 0)) tma2d(sb + st * G_STAGE_BYTES + doff, mp, lane == 0 ? kc : fix, lane == 0 ? fix : kc, fb);
                    __syncwarp();
                    if (!ready && kb == G_STAGES - 1) {
                        if (lane == 0) {
                            wait_flag(flag, target);
                            fence_async_all();
                            for (int j = 0; j < G_STAGES; j++) {
                                const uint32_t s2 = (it + 1 + j) % G_STAGES;
                                tma2d(sb + s2 * G_STAGE_BYTES + doff, mp, (k0 + j) * 64, fix, bar + 8 * s2);
                            }
                        }
                        __syncwarp();
                    }
                }
            }
        }
    } else {
        asm volatile("setmaxnreg.inc.sync.aligned.u32 232;");
        const int wg = warp >> 2, g = lane >> 2, q = lane & 3;
        const bool od = q & 1;
        const int cofs = od ? 8 + 2 * (q - 1) : 2 * q;
        uint32_t it = 0;
        for (uint32_t n = 0;; n++) {
            mbar_wait_long(bar + 64 + 8 * (n & 1), (n >> 1) & 1);
            const uint32_t tw = lds1(bar + 96 + 4 * (n & 1));
            __syncwarp();
            if (lane == 0) mbar_arrive(bar + 80 + 8 * (n & 1));
            if (tw == 0xFFFFFFFFu) break;
            const int kind = tw & 3, tb = (tw >> 2) & 15, nn = (tw >> 6) & 15, part = (tw >> 10) & 63, half = (tw >> 16) & 3;
            const bool act = half == 0 || half == wg + 1;
            const int row = tb * 128 + wg * 64 + (warp & 3) * 16 + g;
            if (kind == 0) {
                float acc[128];
                #pragma unroll
                for (int i = 0; i < 128; i++) acc[i] = 0.f;
                for (int kb = 0; kb < 10; kb++, it++) {
                    const uint32_t st = it % G_STAGES, base = sb + st * G_STAGE_BYTES;
                    mbar_wait_long(bar + 8 * st, (it / G_STAGES) & 1);
                    const uint64_t da = mkdesc(base + wg * 8192, 16, 1024, 1), db = mkdesc(base + 16384, 8192, 1024, 1);
                    wg_fence();
                    #pragma unroll
                    for (int j = 0; j < 4; j++) wg_g256(acc, da + 2 * j, db + 128 * j);
                    wg_commit();
                    if (kb > 0) { wg_wait<1>(); if (lane == 0) mbar_arrive(bar + 32 + 8 * ((it - 1) % G_STAGES)); }
                }
                wg_wait<0>();
                if (lane == 0) mbar_arrive(bar + 32 + 8 * ((it - 1) % G_STAGES));
                bf16* hp = g_h + (size_t)row * FF + nn * 128 + cofs;
                #pragma unroll
                for (int j = 0; j < 16; j += 2)
                    #pragma unroll
                    for (int h = 0; h < 2; h++) {
                        uint32_t w[2];
                        #pragma unroll
                        for (int e = 0; e < 2; e++) {
                            const int i = 4 * (j + e) + 2 * h;
                            const uint32_t gw = pack2(acc[i], acc[i + 1]), uw = pack2(acc[64 + i], acc[65 + i]);
                            w[e] = pack2(bf_lo(gw) * bf_lo(uw), bf_hi(gw) * bf_hi(uw));
                        }
                        const uint32_t r = __shfl_xor_sync(~0u, od ? w[0] : w[1], 1);
                        *reinterpret_cast<uint2*>(hp + (size_t)h * 8 * FF + 8 * j) = od ? make_uint2(r, w[1]) : make_uint2(w[0], r);
                    }
                fence_async_all();
                __threadfence();
                bar_sync(1, 256);
                if (tid == 0) { atomicAdd(&g_fl.h_ready[tb], 1u); }
            } else if (kind == 2 && !act) {
                for (int kb = 0; kb < 6; kb++, it++) {
                    mbar_wait_long(bar + 8 * (it % G_STAGES), (it / G_STAGES) & 1);
                    if (lane == 0) mbar_arrive(bar + 32 + 8 * (it % G_STAGES));
                }
                bar_sync(1, 256);
                if (tid == 0) { atomicAdd(&g_fl.tile[tb * 2 + nn], 1u); }
            } else if (kind != 3) {
                float acc[160];
                #pragma unroll
                for (int i = 0; i < 160; i++) acc[i] = 0.f;
                const int nk = kind == 1 ? 24 : 96 / osplit(tb);
                for (int kb = 0; kb < nk; kb++, it++) {
                    const uint32_t st = it % G_STAGES, base = sb + st * G_STAGE_BYTES;
                    mbar_wait_long(bar + 8 * st, (it / G_STAGES) & 1);
                    const uint64_t da = mkdesc(base + wg * 8192, 16, 1024, 1), db = mkdesc(base + 16384, 8192, 1024, 1);
                    wg_fence();
                    #pragma unroll
                    for (int j = 0; j < 4; j++) { wg_g192(acc, da + 2 * j, db + 128 * j); wg_g128(acc + 96, da + 2 * j, db + 1536 + 128 * j); }
                    wg_commit();
                    if (kb > 0) { wg_wait<1>(); if (lane == 0) mbar_arrive(bar + 32 + 8 * ((it - 1) % G_STAGES)); }
                }
                wg_wait<0>();
                if (lane == 0) mbar_arrive(bar + 32 + 8 * ((it - 1) % G_STAGES));
                int sl = 0;
                for (int i = 0; i < tb; i++) sl += 2 * (osplit(i) + 1);
                sl += nn * (osplit(tb) + 1) + (kind == 1 ? 0 : 1 + part);
                uint4* pp = g_ps + (size_t)sl * 5120 + tid;
                #pragma unroll
                for (int j = 0; j < 20; j++)
                    pp[j * 256] = make_uint4(pack2(acc[8 * j], acc[8 * j + 1]), pack2(acc[8 * j + 2], acc[8 * j + 3]), pack2(acc[8 * j + 4], acc[8 * j + 5]), pack2(acc[8 * j + 6], acc[8 * j + 7]));
                __threadfence();
                bar_sync(1, 256);
                if (tid == 0) {
                    atomicAdd(&g_fl.tile[(tb + (half == 1)) * 2 + nn], 1u);
                    if (kind == 1 && tb == NTB - 1) atomicAdd(&g_fl.tile[NTB * 2 + nn], 1u);
                }
            } else {
                const int np = osplit(tb) + 1, jn = 40 / rsplit(tb), j0 = part * jn;
                int sl = 0;
                for (int i = 0; i < tb; i++) sl += 2 * (osplit(i) + 1);
                const uint4* pp = g_ps + (size_t)(sl + nn * np) * 5120 + tid;
                const size_t off0 = (size_t)row * DM + nn * 320 + cofs;
                if (np == 3) reduce_cols<3, 10>(pp, x + off0, out + off0, j0, jn, od);
                else if (np == 5) reduce_cols<5, 5>(pp, x + off0, out + off0, j0, jn, od);
                else if (np == 9) reduce_cols<9, 4>(pp, x + off0, out + off0, j0, jn, od);
                else if (act) reduce_cols<17, 1>(pp, x + off0, out + off0, j0, jn, od);
            }
        }
        bar_sync(1, 256);
        if (tid == 0) {
            __threadfence();
            if (atomicAdd(&g_fl.done, 1u) == gridDim.x - 1) {
                asm volatile("griddepcontrol.wait;" ::: "memory");
                g_fl.task = 0; g_fl.done = 0;
                for (int i = 0; i <= NTB; i++) { g_fl.o_ready[i] = 0; g_fl.h_ready[i % NTB] = 0; g_fl.tile[2 * i] = 0; g_fl.tile[2 * i + 1] = 0; }
            }
        }
    }
}
constexpr int CS = 15, NCL = 7;
constexpr int VN1 = 7;
constexpr uint32_t SM_V = 0, SM_WO = 81920, SM_XB = 155648, SM_KB = 206848, SM_QB = 211968, SM_SMR = 217344,
                   SM_OMR = 221184, SM_STR = 223232, SM_RSR = 225792, SM_BAR = 231552, SM_TOTAL = 231808;
enum { B_WF0 = 0, B_WF1, B_XF, B_MW0, B_MW1, B_MW2, B_MW3, B_SM, B_OMP, B_RS0, B_RS1, B_RS2, B_RS3,
       B_VD, B_QF, B_ST, B_PT, B_STG, B_OD, B_PC0, B_COUNT = B_PC0 + 10 };
enum { N_QK = 1, N_K1, N_VGO, N_VG2, N_PM, N_OMO, N_CH0, N_CH1, N_WOD, N_T1, N_T2, N_P0, N_P1 };

__device__ __align__(128) bf16 g_xn[S_TOK * DM];
__device__ __align__(1024) bf16 g_xt[S_TOK * DM];
__device__ __align__(128) bf16 g_o[S_TOK * HD];
__device__ __align__(1024) uint32_t g_part2[2 * 4 * 3 * 4 * 32 * 64];
__device__ __align__(1024) uint32_t g_part[2 * 4 * 12 * 8 * 64];

struct Gates { int g[4], x4, sh; };

__device__ __forceinline__ float warp_max(float x) {
    int k = __float_as_int(x); k ^= (k >> 31) & 0x7FFFFFFF;
    k = __reduce_max_sync(~0u, k); k ^= (k >> 31) & 0x7FFFFFFF;
    return __int_as_float(k);
}
__device__ __forceinline__ float warp_sum01(float p) {
    return (float)__reduce_add_sync(~0u, __float2uint_rn(p * 67108864.f)) * (1.f / 67108864.f);
}

__device__ __forceinline__ uint2 poll_sum(uint2 own, const uint32_t* P, uint32_t tag, int cl, uint32_t tgo) {
    uint2 u[NCL];
    #pragma unroll
    for (int i = 0; i < NCL; i++) { u[i] = own; asm volatile("" : "+r"(u[i].x), "+r"(u[i].y)); }
    while ((int)(clk32() - tgo) < 0);
    #pragma unroll
    for (int i = 0; i < NCL; i++) ldg_a64_p(i != cl, u[i], P + i * 64);
    uint32_t tries = 0;
    while (true) {
        const uint32_t bad = lop3<0xFE>(lop3<0xFE>(u[0].x ^ tag, u[1].x ^ tag, u[2].x ^ tag), lop3<0xFE>(u[3].x ^ tag, u[4].x ^ tag, u[5].x ^ tag), u[6].x ^ tag);
        const bool any = __any_sync(~0u, bad & 1);
        const uint32_t p0 = hadd2(u[0].x, u[1].x), p1 = hadd2(u[2].x, u[3].x), p2 = hadd2(u[4].x, u[5].x);
        const uint32_t q0 = hadd2(u[0].y, u[1].y), q1 = hadd2(u[2].y, u[3].y), q2 = hadd2(u[4].y, u[5].y);
        uint2 r = make_uint2(pack2((bf_lo(p0) + bf_lo(p1)) + (bf_lo(p2) + bf_lo(u[6].x)), (bf_hi(p0) + bf_hi(p1)) + (bf_hi(p2) + bf_hi(u[6].x))),
                             pack2((bf_lo(q0) + bf_lo(q1)) + (bf_lo(q2) + bf_lo(u[6].y)), (bf_hi(q0) + bf_hi(q1)) + (bf_hi(q2) + bf_hi(u[6].y))));
        asm volatile("" : "+r"(r.x), "+r"(r.y));
        if (!any) return r;
        #pragma unroll
        for (int i = 0; i < NCL; i++) ldg_a64_retry(u[i], P + i * 64, tag);
        if (++tries > 1000000) __trap();
    }
}

template<bool BIG>
__global__ void __launch_bounds__(512, 1)
w_kernel(const __grid_constant__ CUtensorMap tmQ, const __grid_constant__ CUtensorMap tmK, const __grid_constant__ CUtensorMap tmV,
         const __grid_constant__ CUtensorMap tmO, const __grid_constant__ CUtensorMap tmV2, const __grid_constant__ CUtensorMap tmS, const bf16* __restrict__ mem0, const Gates gts)
{
    extern __shared__ __align__(1024) unsigned char smem[];
    const uint32_t sb = smem_u32(smem);
    uint32_t rank, cl;
    asm("mov.u32 %0, %%cluster_ctarank;" : "=r"(rank));
    asm("mov.u32 %0, %%clusterid.x;" : "=r"(cl));
    const int nh = BIG && cl < 4 ? 5 : 4;
    const int slot = rank / 3, c = rank % 3;
    if (slot >= nh) return;
    const int head = !BIG ? cl : (cl < 4 ? cl * 5 + slot : 20 + (cl - 4) * 4 + slot);
    const int col0 = head * DH + c * 64;
    const int tid = threadIdx.x, warp = __shfl_sync(~0u, tid >> 5, 0);
    if (tid < 6) asm volatile("prefetch.tensormap [%0];" :: "l"((uint64_t)(tid == 0 ? &tmQ : tid == 1 ? &tmK : tid == 2 ? &tmV : tid == 3 ? &tmO : tid == 4 ? &tmV2 : &tmS)) : "memory");
    const uint32_t bar = sb + SM_BAR;
    constexpr uint32_t rstride = 1u << 24;
    if (mapa(sb, 0) != sb - rank * rstride || mapa(sb, 1) - mapa(sb, 0) != rstride || (sb & 0xFFFFFF) != SB0) __trap();
#define REM(r) (((uint32_t)(r) - rank) * rstride)
#define RSPOS(l) ((((l) & 8) << 4) + (((l) & 16) << 1) + (((l) & 7) << 2))
#define RT(d) ((d) | (uint64_t)(uint32_t)zs)
#define OPQ(x) asm volatile("" : "+r"(x))
#define BAR(i) (bar + 8u * (i))
    const uint32_t st_bytes = c == 1 ? 2048 : 2560, pt_bytes = c == 2 ? 2 * 768 : 3 * 768;
    if (tid == 0) {
        mbar_init(BAR(B_WF0), 1); mbar_init(BAR(B_WF1), 1); mbar_init(BAR(B_XF), 1);
        for (int i = 0; i < 4; i++) { mbar_init(BAR(B_MW0 + i), 1); mbar_init(BAR(B_RS0 + i), 1); }
        mbar_init(BAR(B_SM), 4); mbar_init(BAR(B_OMP), 1);
        mbar_init(BAR(B_OD), 1); mbar_init(BAR(B_VD), 4); mbar_init(BAR(B_QF), 1);
        mbar_init(BAR(B_ST), 5); mbar_init(BAR(B_PT), 5); mbar_init(BAR(B_STG), 8);
        mbar_expect_tx(BAR(B_SM), 2560); mbar_expect_tx(BAR(B_OMP), 2048);
        mbar_expect_tx(BAR(B_RS0), 3 * nh * 128);
        for (int i = 1; i < 4; i++) mbar_expect_tx(BAR(B_RS0 + i), slot == 4 ? 1920 : nh * 256);
        mbar_expect_tx(BAR(B_ST), st_bytes);
        mbar_expect_tx(BAR(B_PT), pt_bytes);
        for (int i = 0; i < 10; i++) { mbar_init(BAR(B_PC0 + i), 1); mbar_expect_tx(BAR(B_PC0 + i), 16384); }
        mbar_expect_tx(BAR(B_WF0), 8192); mbar_expect_tx(BAR(B_WF1), 81920 + 73728); mbar_expect_tx(BAR(B_XF), 40960);
        asm volatile("fence.mbarrier_init.release.cluster;" ::: "memory");
    }
    for (int i = tid; i < 5760 / 4; i += 512) sts1(sb + SM_RSR + i * 4, 0u);
    __syncthreads();
    fence_async_smem();
    asm volatile("barrier.cluster.arrive.relaxed.aligned;" ::: "memory");
    if ((tid & 31) == 0) {
        if (warp < 10) tma2d(sb + (warp & 1) * 81920 + (warp >> 1) * 16384, (warp & 1) ? &tmK : &tmQ, col0, (warp >> 1) * 128, BAR(B_PC0 + (warp & 1) * 5 + (warp >> 1)));
        else if (warp == 10) tma2d(sb + SM_KB, &tmV2, col0, 576, BAR(B_WF0));
        else if (warp == 15) {
            asm volatile("griddepcontrol.wait;" ::: "memory");
            asm volatile("griddepcontrol.launch_dependents;" ::: "memory");
            bulk_g2s(sb + SM_XB + 10240, g_xt, 40960, BAR(B_XF));
        }
    }
    __syncwarp();
    asm volatile("barrier.cluster.wait.aligned;" ::: "memory");
    const uint32_t rp0 = REM(slot * 3 + (c + 1) % 3), rp1 = REM(slot * 3 + (c + 2) % 3);
#define LANE_INIT uint32_t rk_; asm volatile("mov.u32 %0, %%cluster_ctarank;" : "=r"(rk_)); const uint32_t sb = SB0 + (rk_ << 24), bar = sb + SM_BAR; \
    const int lane = __shfl_sync(~0u, (int)threadIdx.x & 31, (int)threadIdx.x & 31); const bool l0 = lane == 0

    if (warp < 8) {
        asm volatile("setmaxnreg.inc.sync.aligned.u32 200;");
        LANE_INIT;
        const int wg = warp >> 2, w = warp & 3;
        uint32_t a[40][4];
        {
            const uint32_t ad = sb + wg * 81920 + (((lane >> 4) * 8 + (lane & 7)) * 128) + (((2 * w + ((lane >> 3) & 1)) ^ (lane & 7)) << 4);
            #pragma unroll
            for (int p = 0; p < 5; p++) {
                mbar_wait(BAR(B_PC0 + wg * 5 + p), 0);
                #pragma unroll
                for (int t = 8 * p; t < 8 * p + 8; t++) ldsm4t(a[t], ad + t * 2048);
                bar_sync(N_P0 + wg, 160);
            }
        }
        if (wg == 1) mbar_arrive_p(l0, BAR(B_STG));
        mbar_wait(BAR(B_STG), 0);
        const uint32_t sta = __shfl_sync(~0u, sb + (wg == 0 ? SM_QB : SM_KB) + (lane & 7) * 128 + (((2 * w + ((lane >> 3) & 1)) ^ (lane & 7)) << 4) + (lane >> 4) * 1024, lane);
        constexpr uint64_t xdesc = cdesc(SM_XB + 10240, 128, 10240, 0);
        constexpr uint64_t kdesc = cdesc(SM_KB, 16, 1024, 1), qdesc = cdesc(SM_QB, 16, 1024, 1);
        constexpr uint64_t bo = cdesc(SM_QB, 128, 128, 0), bp = cdesc(SM_OMR, 128, 128, 0);
        #pragma unroll 1
        for (int s = -1; s < NSEG; s++) {
            int ln = lane; OPQ(ln);
            const uint32_t ph = s & 1;
            const int zs = (s + 1) >> gts.sh;
            if (s >= 0) {
                const bool last = s == NSEG - 1;
                {
                    float e[4][4];
                    #pragma unroll
                    for (int i = 0; i < 16; i++) e[i >> 2][i & 3] = 0.f;
                    constexpr int NB = 3;
                    const uint32_t bfr = sb + SM_XB + ln * 16;
                    uint32_t b[NB][4];
                    bool rdy = false;
                    #pragma unroll
                    for (int i = 0; i < 20 + NB - 1; i++) {
                        if (i < 20) {
                            if (i == 0) { mbar_wait(BAR(B_MW3), ph); }
                            if (i == 6 || i == 12 || i == 18) { if (!rdy) mbar_wait(BAR(B_MW0 + (i / 6) % 3), ph); }
                            if (i == 3 || i == 9 || i == 15) rdy = mbar_test(BAR(B_MW0 + (i / 6 + 1) % 3), ph);
                            const int ch = i >= 18 ? 9 : (i / 6 + 2) % 3 + 3 * ((i % 6) >> 1);
                            ldsm4(b[i % NB], bfr + ch * 1024 + (i & 1) * 512);
                        }
                        if (i >= NB - 1) {
                            const int j = i - (NB - 1), ch = j >= 18 ? 9 : (j / 6 + 2) % 3 + 3 * ((j % 6) >> 1);
                            mma16(e[(j & 1) * 2], a[ch * 4 + (j & 1) * 2], b[j % NB][0], b[j % NB][1]);
                            mma16(e[(j & 1) * 2 + 1], a[ch * 4 + (j & 1) * 2 + 1], b[j % NB][2], b[j % NB][3]);
                        }
                    }
                    #pragma unroll
                    for (int i = 0; i < 4; i++) { e[0][i] += e[2][i]; e[1][i] += e[3][i]; }
                    stsm2t(sta, pack2(e[0][0] + e[1][0], e[0][1] + e[1][1]), pack2(e[0][2] + e[1][2], e[0][3] + e[1][3]));
                }
                if (wg == 0) {
                    uint32_t ka = sb + SM_KB + w * 2048 + (ln & 15) * 128 + (((ln >> 4) ^ (ln & 7)) << 4);
                    uint32_t qa = sb + SM_QB + (ln & 7) * 128 + (((ln >> 3) ^ (ln & 7)) << 4);
                    const uint32_t off = sb + SM_SMR + c * 1280 + w * 512 + (ln ^ (ln >> 3)) * (w == 2 ? 8 : 16);
                    const uint32_t o0 = off + rp0, o1 = off + rp1;
                    OPQ(ka); OPQ(qa);
                    bar_sync(N_QK, 256);
                    if (w < 3) {
                        uint32_t b0[4], b1[4], k0[4], k1[4], k2[4], k3[4];
                        float sp[4] = {0.f, 0.f, 0.f, 0.f}, sq[4] = {0.f, 0.f, 0.f, 0.f};
                        ldsm4(b0, qa); ldsm4(k0, ka); ldsm4(k1, ka ^ 32); ldsm4(b1, qa ^ 64); ldsm4(k2, ka ^ 64); ldsm4(k3, ka ^ 96);
                        mma16(sp, k0, b0[0], b0[1]); mma16(sq, k1, b0[2], b0[3]);
                        mma16(sp, k2, b1[0], b1[1]); mma16(sq, k3, b1[2], b1[3]);
                        const uint32_t x0 = fu(sp[0] + sq[0]), x1 = fu(sp[1] + sq[1]), x2 = fu(sp[2] + sq[2]), x3 = fu(sp[3] + sq[3]);
                        if (w < 2) { st_async4(o0, x0, x1, x2, x3, BAR(B_SM) + rp0); st_async4(o1, x0, x1, x2, x3, BAR(B_SM) + rp1); sts4(off, x0, x1, x2, x3); }
                        else { st_async2(o0, x0, x1, BAR(B_SM) + rp0); st_async2(o1, x0, x1, BAR(B_SM) + rp1); sts2(off, x0, x1); }
                        __syncwarp();
                        mbar_arrive_p(l0, BAR(B_SM));
                    }
                    bar_arrive(N_K1, 384);
                    #pragma unroll 1
                    for (int pass = 0; pass < 2; pass++) {
                        const int m = pass ? c : 0;
                        const uint32_t R = sb + (pass ? SM_STR : SM_SMR), O = sb + (pass ? SM_QB + 1024 * (4 - c) : SM_SMR + 2560);
                        const uint32_t e8 = ((ln & 7) * 4 + (w ^ ((ln >> 1) & 3))) * 8, e16 = e8 * 2 + (ln & 8);
                        uint32_t offA = (ln & 16) * 32 + ((m == 2 && ln >= 16) ? e8 : e16), offB = m == 0 ? 1024 + e8 : e16;
                        OPQ(offA); OPQ(offB);
                        mbar_wait(BAR(pass ? B_ST : B_SM), ph);

                        const uint32_t RA = R + (m == 2 ? 512 : 0), OB = O - (m == 2 ? 1024 : 0);
                        const uint2 x0 = lds2(RA + offA), x1 = lds2(RA + 1280 + offA), x2 = lds2(O + offA), y0 = lds2(R + offB), y1 = lds2(R + 1280 + offB), y2 = lds2(OB + offB);
                        if (pass == 0) bar_arrive(N_VG2, 384);
                        bar_sync(N_T1, 128);
                        const int rel = (pass ? 2 * w : 8) - ln;
                        const int limA = 32 - 8 * m + rel, limB = m == 0 ? (ln < 8 ? rel : -2) : (m == 2 ? 8 + rel : -2);
                        const float sc2 = 0.07216878364870322f * 1.4426950408889634f, NEG = -1.0e9f * 1.4426950408889634f;
                        const float a0 = limA >= 0 ? (uf(x0.x) + uf(x1.x) + uf(x2.x)) * sc2 : NEG, a1 = limA >= -1 ? (uf(x0.y) + uf(x1.y) + uf(x2.y)) * sc2 : NEG;
                        const float b0 = limB >= 0 ? (uf(y0.x) + uf(y1.x) + uf(y2.x)) * sc2 : NEG, b1 = limB >= -1 ? (uf(y0.y) + uf(y1.y) + uf(y2.y)) * sc2 : NEG;
                        float ma0 = warp_max(a0), ma1 = warp_max(a1), mb0 = warp_max(b0), mb1 = warp_max(b1);
                        if (m == 0) { ma0 = mb0 = fmaxf(ma0, mb0); ma1 = mb1 = fmaxf(ma1, mb1); }
                        const float pa0 = ex2(a0 - ma0), pa1 = ex2(a1 - ma1), pb0 = ex2(b0 - mb0), pb1 = ex2(b1 - mb1);
                        float sa0 = warp_sum01(pa0), sa1 = warp_sum01(pa1), sb0 = warp_sum01(pb0), sb1 = warp_sum01(pb1);
                        if (m == 0) { sa0 = sb0 = sa0 + sb0; sa1 = sb1 = sa1 + sb1; }
                        const uint32_t wa = pack2(pa0 * rcp_approx(sa0), pa1 * rcp_approx(sa1));
                        uint32_t wb = pack2(pb0 * rcp_approx(sb0), pb1 * rcp_approx(sb1));
                        const uint32_t pa = O + ln * 16 + w * 4;
                        sts1(pa, wa);
                        if (m == 2) { sts1(pa - 1024, wb); if (ln < 16) sts1(pa - 512, 0u); }
                        if (m != 0) wb = 0u;
                        if (ln < 16) sts1(pa + 512, wb);
                        if (pass == 0) { bar_arrive(N_PM, 256); mbar_expect_tx_p(l0 && w == 0, BAR(B_SM), 2560); }
                    }
                    fence_async_smem();
                    bar_sync(N_T2, 128);
                    mbar_arrive_p(l0, BAR(B_PT));
                    if (w < 2 || c == 2) {
                        const uint32_t src = sb + SM_QB + (w < 2 ? 1024 * (4 - c) : 1024) + (w & 1) * 384 + ln * 16;
                        if (ln < 24) {
                            const uint4 u = lds4(src);
                            st_async4(src + rp0, u.x, u.y, u.z, u.w, BAR(B_PT) + rp0); st_async4(src + rp1, u.x, u.y, u.z, u.w, BAR(B_PT) + rp1);
                        }
                        __syncwarp();
                    }
                } else {
                    float d[16];
                    bar_arrive(N_QK, 256);
                    fence_async_smem();
                    bar_sync(N_K1, 384);
                    wg_fence();
                    #pragma unroll
                    for (int k = 0; k < 4; k++) wg_kk32(d, kdesc + 2 * k, qdesc + 64 + 2 * k, k > 0);
                    wg_commit();
                    wg_wait<0>();
                    bar_sync(N_VG2, 384);
                    const int lt = ln ^ (ln >> 3);
                    #pragma unroll
                    for (int j = 0; j < 4; j++) {
                        const int oc = j == 3 ? 0 : (j == 2 ? 1 : 2);
                        const bool full = 2 * w + 1 <= j + 1, half = 2 * w == j + 1;
                        const bool own = oc == c, to0 = oc == (c + 1) % 3;
                        const uint32_t rp = to0 ? rp0 : rp1;
                        const uint32_t dst = (own ? sb + SM_QB + 1024 * (1 + j) : sb + SM_STR + (to0 ? 1280 : 0) + (j == 1 ? 512 : 0) + rp) + w * 512;
                        sts4_p(full && own, dst + lt * 16, fu(d[4 * j]), fu(d[4 * j + 1]), fu(d[4 * j + 2]), fu(d[4 * j + 3]));
                        st_async4_p(full && !own, dst + lt * 16, fu(d[4 * j]), fu(d[4 * j + 1]), fu(d[4 * j + 2]), fu(d[4 * j + 3]), BAR(B_ST) + rp);
                        if (j & 1) {
                            sts2_p(half && own, dst + lt * 8, fu(d[4 * j]), fu(d[4 * j + 1]));
                            st_async2_p(half && !own, dst + lt * 8, fu(d[4 * j]), fu(d[4 * j + 1]), BAR(B_ST) + rp);
                        }
                    }
                    __syncwarp();
                    mbar_arrive_p(l0, BAR(B_ST));
                }
                if (!last && wg == 1) {
                    float d[8];
                    constexpr uint64_t odesc = cdesc(SM_WO, 16, 1024, 1);
                    const uint32_t rr = BIG ? REM(w * 3 + c) : 0;
                    uint32_t rsd = sb + SM_RSR + 1920 + (BIG ? slot : w) * 256 + RSPOS(ln) + rr, rsb = BAR(B_RS1) + rr; OPQ(rsd); OPQ(rsb);
                    bar_sync(N_OMO, 256);
                    wg_fence();
                    #pragma unroll
                    for (int k = 0; k < 4; k++) { wg_ss8(d, odesc + k * 128, bo + k * 16, k > 0); wg_ss8(d + 4, odesc + 1536 + k * 128, bo + k * 16, k > 0); }
                    mbar_wait(BAR(B_OMP), ph); fence_async_smem();
                    wg_fence();
                    #pragma unroll
                    for (int k = 0; k < 8; k++) { wg_ss8_a(d, odesc + 512 + k * 128, bp + k * 16); wg_ss8_a(d + 4, odesc + 2048 + k * 128, bp + k * 16); }
                    wg_commit();
                    wg_wait<0>();
                    st_async1(rsd, pack2(d[0], d[1]), rsb); st_async1(rsd + 64, pack2(d[2], d[3]), rsb);
                    st_async1(rsd + 1280, pack2(d[4], d[5]), rsb + 8); st_async1(rsd + 1344, pack2(d[6], d[7]), rsb + 8);
                    bar_arrive(N_CH0, 256);
                }
            }
            if (s + 1 < NSEG) {
                float d[16];
                mbar_wait(BAR(B_XF), ph ^ 1);
                {
                    const uint32_t tfr = sb + SM_XB + 10240 + (ln >> 4) * 10240 + (ln & 15) * 16;
                    uint32_t b0[4], b1[4];
                    ldsm4(b0, tfr); ldsm4(b1, tfr + 20480);
                    #pragma unroll
                    for (int i = 0; i < 16; i++) d[i] = 0.f;
                    mma16(d, a[0], b0[0], b0[1]); mma16(d + 4, a[0], b0[2], b0[3]);
                    mma16(d + 8, a[0], b1[0], b1[1]); mma16(d + 12, a[0], b1[2], b1[3]);
                }
                asm volatile("" :: "f"(d[0]), "f"(d[4]), "f"(d[8]), "f"(d[12]) : "memory");
                bar_sync(N_WOD, 256);

                wg_fence();
                #pragma unroll
                for (int t = 1; t < 40; t++) wg_rs32_a(d, a[t], (t < 4 ? xdesc : RT(cdesc(SM_XB + 10240, 128, 10240, 0))) + (uint64_t)(t * 16));
                wg_commit();
                wg_wait<0>();

                if (s >= 0 && wg == 0) mbar_wait(BAR(B_QF), ph);
                stsm4t(sta + 1024, pack2(d[0], d[1]), pack2(d[2], d[3]), pack2(d[4], d[5]), pack2(d[6], d[7]));
                stsm4t(sta + 3072, pack2(d[8], d[9]), pack2(d[10], d[11]), pack2(d[12], d[13]), pack2(d[14], d[15]));
                fence_async_smem();
            }
        }
    } else if (warp < 12) {
        asm volatile("setmaxnreg.dec.sync.aligned.u32 72;");
        LANE_INIT;
        const int w = warp & 3;
        uint32_t a9[4][4];
        mbar_wait(BAR(B_WF0), 0);
        {
            const uint32_t ad = sb + SM_KB + (((lane >> 4) * 8 + (lane & 7)) * 128) + (((2 * w + ((lane >> 3) & 1)) ^ (lane & 7)) << 4);
            #pragma unroll
            for (int t = 0; t < 4; t++) ldsm4t(a9[t], ad + t * 2048);
        }
        mbar_arrive_p(l0, BAR(B_STG));
        constexpr uint64_t vdesc = cdesc(SM_V, 16, 1024, 1), xdesc = cdesc(SM_XB, 128, 10240, 0);
        constexpr uint64_t odesc = cdesc(SM_WO + 2 * 24576, 16, 1024, 1);
        constexpr uint64_t bo = cdesc(SM_QB, 128, 128, 0), bp = cdesc(SM_OMR, 128, 128, 0);
        constexpr uint64_t pdesc = cdesc(SM_QB + 1024, 128, 1024, 0);
        const bool t0 = l0 && w == 0;
        mbar_wait(BAR(B_WF1), 0);
        #pragma unroll 1
        for (int s = 0; s < NSEG; s++) {
            const bool last = s == NSEG - 1;
            int ln = lane; OPQ(ln);
            const uint32_t l4 = sb + ln * 4;
            const uint32_t ph = s & 1;
            const int zs = s >> gts.sh;
            float v[20];
            bar_sync(N_K1, 384);
            wg_fence();
            #pragma unroll
            for (int t = 0; t < VN1; t++) wg_ss40(v, vdesc + (uint64_t)(t * 128), xdesc + (uint64_t)(t * 16), t > 0);
            #pragma unroll
            for (int t = 0; t < 4; t++) wg_rs40_a(v, a9[t], xdesc + (uint64_t)((36 + t) * 16));
            bar_sync(N_VG2, 384);
            wg_fence();
            #pragma unroll
            for (int t = VN1; t < 36; t++)
                wg_ss40_a(v, (t < VN1 + 2 ? vdesc : RT(cdesc(SM_V, 16, 1024, 1))) + (uint64_t)(t * 128), (t < VN1 + 2 ? xdesc : RT(cdesc(SM_XB, 128, 10240, 0))) + (uint64_t)(t * 16));
            wg_commit();
            uint32_t va[3][4];
            if (!last) {
                const uint32_t off = l4 + w * 256;
                const uint32_t o0 = off + SM_OMR + 1024 + rp0, o1 = off + SM_OMR + rp1;
                bar_sync(N_PM, 256);
                uint32_t pb[6];
                ldsm4t(pb, sb + SM_SMR + 2560 + ln * 16); ldsm2t(pb + 4, sb + SM_SMR + 3072 + ln * 16);
                wg_wait<0>();
                mbar_arrive_p(l0, BAR(B_VD));
                #pragma unroll
                for (int j = 0; j < 10; j++) va[j >> 2][j & 3] = pack2(v[2 * j], v[2 * j + 1]);
                va[2][2] = 0u; va[2][3] = 0u;
                float oa[4] = {0.f, 0.f, 0.f, 0.f}, ob[4] = {0.f, 0.f, 0.f, 0.f}, oc[4] = {0.f, 0.f, 0.f, 0.f};
                mma16(oa, va[0], pb[0], pb[1]);
                mma16(ob, va[1], pb[2], pb[3]);
                mma8v(oc, va[2][0], va[2][1], pb[4]);
                const uint32_t y0 = pack2(oa[0] + ob[0] + oc[0], oa[1] + ob[1] + oc[1]), y1 = pack2(oa[2] + ob[2] + oc[2], oa[3] + ob[3] + oc[3]);
                sts1(off + SM_QB, y0); sts1(off + SM_QB + 128, y1);
                st_async1(o0, y0, BAR(B_OMP) + rp0); st_async1(o0 + 128, y1, BAR(B_OMP) + rp0);
                st_async1(o1, y0, BAR(B_OMP) + rp1); st_async1(o1 + 128, y1, BAR(B_OMP) + rp1);
                fence_async_smem();
                const bool s4 = BIG && nh == 5;
                const uint32_t r0 = REM(s4 ? 12 + (2 * w) % 3 : (BIG ? w * 3 : 0)), r1 = REM(s4 ? 12 + (2 * w + 1) % 3 : (BIG ? w * 3 + 1 : 1));
                const uint32_t j0 = s4 ? (2 * w) / 3 : 0, j1 = s4 ? (2 * w + 1) / 3 : 0;
                const uint32_t rs0 = l4 + SM_RSR + (BIG ? rank : w * 3 + rank) * 128;
                const uint32_t rr = BIG ? REM(w * 3 + c) : 0;
                const uint32_t rsd = sb + RSPOS(ln) + SM_RSR + 1920 + 2560 + (BIG ? slot : w) * 256 + rr, rsb = BAR(B_RS3) + rr;
                bar_sync(N_OMO, 256);
                float d9[4], d[8];
                wg_fence();
                #pragma unroll
                for (int k = 0; k < 4; k++) { wg_ss8(d9, vdesc + (36 + k) * 128, bo + k * 16, k > 0); wg_ss8(d + (k & 1) * 4, odesc + k * 128, bo + k * 16, k > 1); }
                mbar_wait(BAR(B_OMP), ph); fence_async_smem();
                wg_fence();
                #pragma unroll
                for (int k = 0; k < 8; k++) wg_ss8_a(d + (k & 1) * 4, odesc + 512 + k * 128, bp + k * 16);
                wg_commit();
                mbar_expect_tx_p(t0, BAR(B_OMP), 2048);
                wg_wait<0>();
                st_async1(rsd, pack2(d[0] + d[4], d[1] + d[5]), rsb);
                st_async1(rsd + 64, pack2(d[2] + d[6], d[3] + d[7]), rsb);
                st_async1(rs0 + j0 * 1920 + r0, pack2(d9[0], d9[1]), BAR(B_RS0 + j0) + r0);
                st_async1(rs0 + j1 * 1920 + r1, pack2(d9[2], d9[3]), BAR(B_RS0 + j1) + r1);
            } else {
                bar_sync(N_PM, 256);
                wg_wait<0>();
                #pragma unroll
                for (int j = 0; j < 10; j++) va[j >> 2][j & 3] = pack2(v[2 * j], v[2 * j + 1]);
                va[2][2] = 0u; va[2][3] = 0u;
            }
            float dd[16];
            mbar_wait(BAR(B_PT), ph);
            fence_async_smem();
            wg_fence();
            wg_rt32_z(dd, va[0], pdesc); wg_rt32_a(dd, va[1], pdesc + 16); wg_rt32_a(dd, va[2], pdesc + 32);
            wg_commit();
            mbar_expect_tx_p(t0, BAR(B_ST), st_bytes); mbar_expect_tx_p(t0, BAR(B_PT), pt_bytes);
            wg_wait<0>();
            if (!last) bar_sync(N_CH0, 256);
            {
                const uint32_t sa = sb + SM_OMR + (ln & 7) * 128 + (((2 * w + ((ln >> 3) & 1)) ^ (ln & 7)) << 4) + (ln >> 4) * 1024;
                stsm4t(sa, pack2(dd[0], dd[1]), pack2(dd[2], dd[3]), pack2(dd[4], dd[5]), pack2(dd[6], dd[7]));
                stsm4t(sa + 2048, pack2(dd[8], dd[9]), pack2(dd[10], dd[11]), pack2(dd[12], dd[13]), pack2(dd[14], dd[15]));
            }
            fence_async_smem();
            bar_sync(N_VGO, 128);
            if (t0) {
                fence_async_smem();
                asm volatile("cp.async.bulk.tensor.2d.global.shared::cta.bulk_group [%0, {%2, %3}], [%1];" :: "l"((uint64_t)&tmS), "r"(sb + SM_OMR), "r"(col0), "r"(s * 32) : "memory");
                asm volatile("cp.async.bulk.commit_group;" ::: "memory");
                asm volatile("cp.async.bulk.wait_group.read 0;" ::: "memory");
                mbar_arrive(BAR(B_QF));
                if ((s & 3) == 3 || s == NSEG - 3) { asm volatile("cp.async.bulk.wait_group 0;" ::: "memory"); mbar_arrive(BAR(B_OD)); }
            }
            __syncwarp();
        }
    } else {
        asm volatile("setmaxnreg.dec.sync.aligned.u32 40;");
        LANE_INIT;
        const int w = warp & 3;
        uint4 m0[5];
        #pragma unroll
        for (int i = 0; i < 5; i++) { const int j = i * 128 + w * 32 + lane; m0[i] = *reinterpret_cast<const uint4*>(mem0 + (j & 7) * DM + (j >> 3) * 8); }
        if (w < 2) {
            #pragma unroll 1
            for (int p = 0; p < 5; p++) {
                bar_sync(N_P0 + w, 160);
                fence_async_smem();
                const int i = 2 * p + lane;
                if (w == 0) {
                    if (l0) tma2d(sb + SM_V + p * 16384, p < 4 ? &tmV : &tmV2, col0, p * 128, BAR(B_WF1));
                    if (lane == 1 && p == 4) tma2d(sb + SM_V + 73728, &tmO, 576, col0, BAR(B_WF1));
                }
                else if (lane < 2 && i < 9) tma2d(sb + SM_WO + i * 8192, &tmO, (3 * c + i / 3) * 64, head * DH + ((c + i % 3) % 3) * 64, BAR(B_WF1));
                __syncwarp();
            }
        }
        mbar_wait(BAR(B_STG), 0);
        #pragma unroll
        for (int i = 0; i < 5; i++) sts4(sb + SM_XB + (i * 128 + w * 32 + lane) * 16, m0[i].x, m0[i].y, m0[i].z, m0[i].w);
        fence_async_smem();
        bar_sync(N_CH1, 128);
        mbar_arrive_p(l0, BAR(B_MW0 + w));
        const int wv = slot == 4 ? 0 : w, hb = slot == 4 ? 3 * w + c : 2 * slot + c;
        const bool owner = slot == 4 ? hb < 8 : (w > 0 || (c < 2 && (!BIG || nh == 4)));
        auto publish = [&](int tb, uint32_t par) {
            mbar_wait(BAR(B_OD), par);
            fence_async_all();
            __threadfence();
            if (l0) { atomicAdd(&g_fl.o_ready[tb], 1u); }
            __syncwarp();
        };
        uint32_t* const pbase = g_part + (wv > 0 ? wv * 12 + rank : hb) * 512;
        const int gate = (nh == 5 ? 0 : gts.x4) + (wv == 0 ? gts.g[0] : (wv == 1 ? gts.g[1] : (wv == 2 ? gts.g[2] : gts.g[3])));
        #pragma unroll 1
        for (int s = 0; s < NSEG; s++) {
            const bool last = s == NSEG - 1;
            int ln = lane; OPQ(ln);
            const uint32_t ph = s & 1;
            if (w == 1 && s > 0 && ((s & 3) == 0 || s == NSEG - 2)) publish(s == NSEG - 2 ? NTB : (s >> 2) - 1, s == NSEG - 2 ? 1 : ((s >> 2) - 1) & 1);
            if (w == 3) {
                if (!last) {
                    mbar_wait(BAR(B_VD), ph);
                    mbar_expect_tx_p(ln < 4, BAR(B_MW0) + ln * 8, ln == 0 ? 1024 : 3072);
                    if (l0) { mbar_expect_tx(BAR(B_XF), 40960); bulk_g2s(sb + SM_XB + 10240, g_xt + (size_t)(s + 1) * 32 * DM, 40960, BAR(B_XF)); }
                    __syncwarp();
                }
            }
            if (!owner) continue;
            const uint32_t tag = ((s >> 1) & 1) ^ 1;
            if (!BIG) {
                uint32_t* Q = g_part2 + ((((s & 1) * 4 + w) * 3 + c) * 4) * 2048 + ln * 2;
                if (!last) mbar_wait(BAR(B_RS0 + w), ph);
                #pragma unroll 1
                for (int b = 0; b < 4; b++) {
                    uint32_t u[4], x, y;
                    if (w > 0) { ldsm4t(u, sb + SM_RSR + 1920 + (w - 1) * 1280 + b * 256 + (ln & 15) * 16); x = u[0]; y = u[1]; }
                    else {
                        ldsm4t(u, sb + SM_RSR + b * 384 + ln * 16);
                        x = pack2(bf_lo(u[0]) + bf_lo(u[1]) + bf_lo(u[2]), bf_hi(u[0]) + bf_hi(u[1]) + bf_hi(u[2]));
                        y = __shfl_down_sync(~0u, x, 1);
                    }
                    stg_a64(Q + b * 2048 + cl * 64, set_tag(uf(x), tag), y);
                }
                if (last) break;
                mbar_expect_tx_p(l0, BAR(B_RS0 + w), w > 0 ? 1024 : 1536);
                #pragma unroll 1
                for (int b = 0; b < 4; b++) {
                    float a0 = 0.f, a1 = 0.f, a2 = 0.f, a3 = 0.f;
                    #pragma unroll 1
                    for (int j = 0; j < 32; j += 8) {
                        uint2 u[8];
                        #pragma unroll
                        for (int i = 0; i < 8; i++) u[i] = make_uint2(tag ^ 1, 0u);
                        uint32_t bad, tries = 0;
                        do {
                            bad = 0;
                            #pragma unroll
                            for (int i = 0; i < 8; i++) ldg_a64_retry(u[i], Q + b * 2048 + (j + i) * 64, tag);
                            #pragma unroll
                            for (int i = 0; i < 8; i++) bad = or_xor(bad, u[i].x, tag);
                            if (++tries > 1000000) __trap();
                        } while (__any_sync(~0u, bad & 1));
                        #pragma unroll
                        for (int i = 0; i < 8; i++) { a0 += bf_lo(u[i].x); a1 += bf_hi(u[i].x); a2 += bf_lo(u[i].y); a3 += bf_hi(u[i].y); }
                    }
                    const uint32_t da = w > 0 ? SB0 + SM_XB + (3 * c + w - 1) * 1024 + b * 256 + (ln & 2) * 64 + (ln >> 2) * 16 + (ln & 1) * 8
                                              : SB0 + SM_XB + 9 * 1024 + (2 * b + c) * 128 + ln * 4;
                    if (w > 0 || !(ln & 1))
                        for (int i = 0; i < 3; i++) st_async2(da + i * rstride, pack2(a0, a1), pack2(a2, a3), SB0 + SM_BAR + 8 * (B_MW0 + w) + i * rstride);
                    __syncwarp();
                }
                continue;
            }
            uint32_t* P = pbase + (s & 1) * (4 * 12 * 512) + ln * 2;
            uint32_t* Pw = P + cl * 64 + (wv > 0 ? ((ln & 2) * 8 + (ln >> 2) * 2 + (ln & 1) - ln) * 2 : 0);
            uint32_t ra = sb + SM_RSR + (wv > 0 ? 640 + w * 1280 : w * 1920) + ln * 16;
            uint32_t da = wv > 0 ? SB0 + SM_XB + (3 * c + w - 1) * 1024 + slot * 256 + ln * 8
                                : SB0 + SM_XB + 9 * 1024 + hb * 128 + ln * 4;
            OPQ(ra); OPQ(da); asm volatile("" : "+l"(P), "+l"(Pw));
            if (!last) mbar_wait(BAR(B_RS0 + w), ph);
            uint2 own;
            {
                uint32_t u0[4], u1[4], u2[4];
                ldsm4t(u0, ra); ldsm4t(u1, ra + 512); ldsm4t(u2, ra + 1024);
                uint32_t x = hadd2(hadd2(hadd2(u0[0], u0[2]), hadd2(u1[0], u1[2])), u2[0]), y = hadd2(hadd2(hadd2(u0[1], u0[3]), hadd2(u1[1], u1[3])), u2[1]);
                if (wv == 0) {
                    ldsm4t(u0, ra + 1536);
                    const uint32_t z = hadd2(hadd2(hadd2(u2[2], u2[3]), hadd2(u0[0], u0[1])), u0[2]);
                    x = pack2(bf_lo(x) + bf_lo(y) + bf_lo(z), bf_hi(x) + bf_hi(y) + bf_hi(z));
                    y = __shfl_down_sync(~0u, x, 1);
                }
                own = make_uint2(set_tag(uf(x), tag), y);
                stg_a64(Pw, own.x, own.y);
            }
            if (last) break;
            const uint32_t tgo = clk32() + gate + (ln >> 5);
            mbar_expect_tx_p(l0, BAR(B_RS0 + w), wv > 0 ? nh * 256 : nh * 384);
            uint32_t db = SB0 + SM_BAR + 8 * (B_MW0 + wv) + (ln >> 5); OPQ(db);
            { const int src = wv > 0 ? ((ln >> 1) & 7) * 4 + (ln >> 4) * 2 + (ln & 1) : ln; own.x = __shfl_sync(~0u, own.x, src); own.y = __shfl_sync(~0u, own.y, src); }
            const uint2 r = poll_sum(own, P, tag, cl, tgo);
            if (wv > 0 || !(ln & 1)) {
                #pragma unroll
                for (int i = CS - 1; i >= 0; i--)
                    if (i < 12 || nh == 5) st_async2(da + i * rstride, r.x, r.y, db + i * rstride);
            }
            __syncwarp();
        }
        if (w == 1) publish(NTB - 1, 0);
    }
    asm volatile("barrier.cluster.arrive.aligned;\nbarrier.cluster.wait.aligned;" ::: "memory");
#undef BAR
#undef REM
}
__global__ void __launch_bounds__(256) ln_kernel(const bf16* __restrict__ x, const char* wq, const char* wk, const char* wv, const char* wo, const char* mem0) {
    __shared__ __align__(16) unsigned char tile[10240];
    asm volatile("griddepcontrol.launch_dependents;" ::: "memory");
    if (blockIdx.x == 0 && threadIdx.x == 0) asm volatile("cp.async.bulk.prefetch.L2.global [%0], 10240;" :: "l"(mem0) : "memory");
    const int row = blockIdx.x * 8 + (threadIdx.x >> 5), lane = threadIdx.x & 31;
    const uint2* xr = reinterpret_cast<const uint2*>(x + (size_t)row * DM);
    float v[20]; float s = 0.f;
    uint2 xu[5];
    #pragma unroll
    for (int i = 0; i < 5; i++) asm volatile("ld.global.nc.v2.u32 {%0,%1}, [%2];" : "=r"(xu[i].x), "=r"(xu[i].y) : "l"(xr + i * 32 + lane) : "memory");
    __syncthreads();
    if (threadIdx.x < 240) {
        const size_t o = (size_t)blockIdx.x * 30720 + threadIdx.x * 128;
        asm volatile("prefetch.global.L2 [%0];" :: "l"(wk + o)); asm volatile("prefetch.global.L2 [%0];" :: "l"(wq + o));
        asm volatile("prefetch.global.L2 [%0];" :: "l"(wv + o)); asm volatile("prefetch.global.L2 [%0];" :: "l"(wo + o));
    }
    #pragma unroll
    for (int i = 0; i < 5; i++) {
        const uint2 u = xu[i];
        v[4 * i] = bf_lo(u.x); v[4 * i + 1] = bf_hi(u.x); v[4 * i + 2] = bf_lo(u.y); v[4 * i + 3] = bf_hi(u.y);
        s += (v[4 * i] + v[4 * i + 1]) + (v[4 * i + 2] + v[4 * i + 3]);
    }
    #pragma unroll
    for (int o = 16; o; o >>= 1) s += __shfl_xor_sync(~0u, s, o);
    const float m = s * (1.f / DM); float q = 0.f;
    #pragma unroll
    for (int i = 0; i < 20; i++) { v[i] -= m; q += v[i] * v[i]; }
    #pragma unroll
    for (int o = 16; o; o >>= 1) q += __shfl_xor_sync(~0u, q, o);
    const float r = rsqrtf(q * (1.f / DM) + 1e-5f);
    uint2* yr = reinterpret_cast<uint2*>(g_xn + (size_t)row * DM);
    #pragma unroll
    for (int i = 0; i < 5; i++) {
        const uint2 o = make_uint2(pack2(v[4 * i] * r, v[4 * i + 1] * r), pack2(v[4 * i + 2] * r, v[4 * i + 3] * r));
        yr[i * 32 + lane] = o;
        const int col = (i * 32 + lane) * 4;
        *reinterpret_cast<uint2*>(tile + (col >> 3) * 128 + (row & 7) * 16 + (lane & 1) * 8) = o;
    }
    __syncthreads();
    uint4* dst = reinterpret_cast<uint4*>(reinterpret_cast<char*>(g_xt) + (size_t)blockIdx.x * 10240);
    for (int i = threadIdx.x; i < 640; i += 256) dst[i] = reinterpret_cast<const uint4*>(tile)[i];
}

typedef CUresult (*EncFn)(CUtensorMap*, CUtensorMapDataType, cuuint32_t, void*, const cuuint64_t*, const cuuint64_t*, const cuuint32_t*, const cuuint32_t*,
                          CUtensorMapInterleave, CUtensorMapSwizzle, CUtensorMapL2promotion, CUtensorMapFloatOOBfill);
static void mk2d(EncFn enc, CUtensorMap* m, const void* p, uint64_t cols, uint64_t rows, uint32_t bc, uint32_t br) {
    cuuint64_t dims[2] = {cols, rows}; cuuint64_t str[1] = {cols * 2}; cuuint32_t box[2] = {bc, br}; cuuint32_t es[2] = {1, 1};
    enc(m, CU_TENSOR_MAP_DATA_TYPE_BFLOAT16, 2, (void*)p, dims, str, box, es, CU_TENSOR_MAP_INTERLEAVE_NONE, CU_TENSOR_MAP_SWIZZLE_128B,
        CU_TENSOR_MAP_L2_PROMOTION_L2_128B, CU_TENSOR_MAP_FLOAT_OOB_FILL_NONE);
}

extern "C" void kernel_launch(void* const* d_in, const int* in_sizes, int n_in, void* d_out, int out_size) {
    (void)in_sizes; (void)n_in; (void)out_size;
    const bf16* x = (const bf16*)d_in[0];
    const bf16* mem0 = (const bf16*)d_in[1];
    void* fn = nullptr; cudaDriverEntryPointQueryResult qr;
    cudaGetDriverEntryPoint("cuTensorMapEncodeTiled", &fn, cudaEnableDefault, &qr);
    EncFn enc = (EncFn)fn;
    void *xn, *ob, *hb;
    cudaGetSymbolAddress(&xn, g_xn); cudaGetSymbolAddress(&ob, g_o); cudaGetSymbolAddress(&hb, g_h);
    CUtensorMap tq, tk, tv, tv2, ts, to, tx, th, toa, toh, tg, tu, td;
    mk2d(enc, &tq, d_in[2], HD, DM, 64, 128); mk2d(enc, &tk, d_in[3], HD, DM, 64, 128); mk2d(enc, &tv, d_in[4], HD, DM, 64, 128);
    mk2d(enc, &to, d_in[5], DM, HD, 64, 64); mk2d(enc, &tv2, d_in[4], HD, DM, 64, 64); mk2d(enc, &ts, ob, HD, S_TOK, 64, 32);
    mk2d(enc, &tx, xn, DM, S_TOK, 64, 128); mk2d(enc, &th, hb, FF, S_TOK, 64, 128); mk2d(enc, &toa, ob, HD, S_TOK, 64, 128); mk2d(enc, &toh, ob, HD, S_TOK, 64, 64);
    mk2d(enc, &tg, d_in[8], FF, DM, 64, 64); mk2d(enc, &tu, d_in[9], FF, DM, 64, 64); mk2d(enc, &td, d_in[10], DM, FF, 64, 64);
    cudaFuncSetAttribute(w_kernel<true>, cudaFuncAttributeMaxDynamicSharedMemorySize, SM_TOTAL);
    cudaFuncSetAttribute(w_kernel<true>, cudaFuncAttributeNonPortableClusterSizeAllowed, 1);
    cudaFuncSetAttribute(w_kernel<false>, cudaFuncAttributeMaxDynamicSharedMemorySize, SM_TOTAL);
    cudaFuncSetAttribute(g_kernel, cudaFuncAttributeMaxDynamicSharedMemorySize, G_SMEM);
    int nsm = 132; cudaDeviceGetAttribute(&nsm, cudaDevAttrMultiProcessorCount, 0);
    cudaStream_t st = cudaStreamPerThread;

    ln_kernel<<<S_TOK / 8, 256, 0, st>>>(x, (const char*)d_in[2], (const char*)d_in[3], (const char*)d_in[4], (const char*)d_in[5], (const char*)d_in[1]);
    {
        cudaLaunchConfig_t cfg = {};
        cfg.gridDim = dim3(CS * NCL); cfg.blockDim = dim3(512); cfg.dynamicSmemBytes = SM_TOTAL; cfg.stream = st;
        cudaLaunchAttribute at[2];
        at[0].id = cudaLaunchAttributeClusterDimension; at[0].val.clusterDim.x = CS; at[0].val.clusterDim.y = 1; at[0].val.clusterDim.z = 1;
        at[1].id = cudaLaunchAttributeProgrammaticStreamSerialization; at[1].val.programmaticStreamSerializationAllowed = 1;
        cfg.attrs = at; cfg.numAttrs = 2;
        Gates gts = {{130, 200, 340, 130}, 130, 10};
        int ncl = 0;
        cfg.numAttrs = 1;
        if (cudaOccupancyMaxActiveClusters(&ncl, w_kernel<true>, &cfg) != cudaSuccess) { ncl = 0; (void)cudaGetLastError(); }
        cfg.numAttrs = 2;
        if (ncl >= NCL) cudaLaunchKernelEx(&cfg, w_kernel<true>, tq, tk, tv, to, tv2, ts, mem0, gts);
        else {
            cfg.gridDim = dim3(96); at[0].val.clusterDim.x = 3;
            cudaLaunchKernelEx(&cfg, w_kernel<false>, tq, tk, tv, to, tv2, ts, mem0, gts);
        }
    }
    {
        cudaLaunchConfig_t cfg = {};
        cfg.gridDim = dim3(nsm); cfg.blockDim = dim3(384); cfg.dynamicSmemBytes = G_SMEM; cfg.stream = st;
        cudaLaunchAttribute at[1];
        at[0].id = cudaLaunchAttributeProgrammaticStreamSerialization; at[0].val.programmaticStreamSerializationAllowed = 1;
        cfg.attrs = at; cfg.numAttrs = 1;
        cudaLaunchKernelEx(&cfg, g_kernel, tx, th, toa, tg, tu, td, to, toh, x, (bf16*)d_out, 96u);
    }
}
```
